```python
import torch

def _softmax(x, axis=-1):
    return torch.softmax(x, dim=axis)

def _gelu(x):
    return torch.nn.functional.gelu(x, approximate='tanh')

def _silu(x):
    return torch.nn.functional.silu(x)

def _sigmoid(x):
    return torch.sigmoid(x)

def _layernorm(x, axis=-1, eps=1e-05):
    m = x.mean(dim=axis, keepdim=True)
    v = x.var(dim=axis, keepdim=True, unbiased=False)
    return (x - m) / torch.sqrt(v + eps)

def _scatter_add(tgt, idx, src, axis=0):
    return tgt.clone().index_add_(axis, idx, src)

def _segment_sum(src, seg, n):
    out = torch.zeros((n,) + src.shape[1:], dtype=src.dtype)
    return out.index_add_(0, seg, src)

def _pad(x, pw):
    flat = tuple((v for pair in reversed(pw) for v in pair))
    return torch.nn.functional.pad(x, flat)
kernel_name = 'interleave_layers__linear_kernel_hedgehog__mixer_gmlp__prompt'

def setup_inputs():

    _w = lambda a: (lambda t: t.to(torch.bfloat16) if t.is_floating_point() else t)(torch.as_tensor(a))

    def _A_setup():
        B, S, D, H = (1, 2048, 640, 32)
        Dh = D // H
        return {'x': _w((lambda *s: torch.randn(*s, dtype=torch.bfloat16) * 0.05)(B, S, D)), 'wqkv': _w((lambda *s: torch.randn(*s, dtype=torch.bfloat16) * 0.4)(D, 3 * D)), 'w_phi': _w((lambda *s: torch.randn(*s, dtype=torch.bfloat16) * 0.4)(H, Dh, Dh) * Dh ** (-0.5)), 'wo': _w((lambda *s: torch.randn(*s, dtype=torch.bfloat16) * 0.05)(D, D))}
    _A_in = _A_setup()

    def _B_setup():
        B, S, D, F = (1, 2048, 640, 1536)
        Fh = F // 2
        return {'x': _w((lambda *s: torch.randn(*s, dtype=torch.bfloat16) * 0.05)(B, S, D)), 'w_in': _w((lambda *s: torch.randn(*s, dtype=torch.bfloat16) * 0.4)(D, 2 * Fh)), 'w_sp': _w(0.01 * (lambda *s: torch.randn(*s, dtype=torch.bfloat16) * 0.4)(S, S)), 'b_sp': _w(1.0 + 0.01 * (lambda *s: torch.randn(*s, dtype=torch.bfloat16) * 0.05)(S)), 'w_out': _w((lambda *s: torch.randn(*s, dtype=torch.bfloat16) * 0.05)(Fh, D))}
    _B_in = _B_setup()
    return {'A_x': _A_in['x'], 'A_wqkv': _A_in['wqkv'], 'A_w_phi': _A_in['w_phi'], 'A_wo': _A_in['wo'], 'B_x': _B_in['x'], 'B_w_in': _B_in['w_in'], 'B_w_sp': _B_in['w_sp'], 'B_b_sp': _B_in['b_sp'], 'B_w_out': _B_in['w_out']}

def reference(A_x, A_wqkv, A_w_phi, A_wo, B_x, B_w_in, B_w_sp, B_b_sp, B_w_out):

    def _A_ref(x, wqkv, w_phi, wo):
        B, S, D = x.shape
        H = 32
        Dh = D // H
        qkv = (lambda x, *d: x.permute(*d))((x @ wqkv).reshape(B, S, 3, H, Dh), 2, 0, 3, 1, 4)
        q, k, v = (qkv[0], qkv[1], qkv[2])
        pq = torch.einsum('bhsd,hdf->bhsf', q, w_phi)
        pk = torch.einsum('bhsd,hdf->bhsf', k, w_phi)
        phi_q = torch.concatenate([_softmax(pq, axis=-1), _softmax(-pq, axis=-1)], axis=-1)
        phi_k = torch.concatenate([_softmax(pk, axis=-1), _softmax(-pk, axis=-1)], axis=-1)
        kv = torch.einsum('bhsf,bhsd->bhfd', phi_k, v)
        z = torch.einsum('bhsf->bhf', phi_k)
        num = torch.einsum('bhqf,bhfd->bhqd', phi_q, kv)
        den = torch.einsum('bhqf,bhf->bhq', phi_q, z)[..., None] + 1e-06
        o = num / den
        return (lambda x, *d: x.permute(*d))(o, 0, 2, 1, 3).reshape(B, S, D) @ wo

    def _B_ref(x, w_in, w_sp, b_sp, w_out):
        B, S, D = x.shape
        F = w_in.shape[-1]
        Fh = F // 2
        z = _gelu(torch.einsum('bsd,df->bsf', x, w_in))
        z1 = z[..., :Fh].clone()
        z2 = _layernorm(z[..., Fh:], axis=-1)
        g = torch.einsum('ts,bsf->btf', w_sp, z2) + b_sp[None, :, None]
        return torch.einsum('bsf,fd->bsd', z1 * g, w_out)
    x = A_x
    x = x + _A_ref(_layernorm(x, axis=-1), A_wqkv, A_w_phi, A_wo)
    x = x + _B_ref(_layernorm(x, axis=-1), B_w_in, B_w_sp, B_b_sp, B_w_out)
    x = x + _A_ref(_layernorm(x, axis=-1), A_wqkv, A_w_phi, A_wo)
    x = x + _B_ref(_layernorm(x, axis=-1), B_w_in, B_w_sp, B_b_sp, B_w_out)
    return x
```

```cpp
#include <cuda_runtime.h>
#include <cuda_bf16.h>
#include <cuda.h>
#include <stdint.h>

#define SLEEP_ST 40
#define SLEEP_XS 200
#define MAPPING 2
#define P3G 1
#define USE_MC 1

#define DBG_AK(k) (k)
#define DBG_BK(k) (k)

namespace {

constexpr int S_ = 2048, D_ = 640, FH_ = 768;
constexpr int NCTA = 128, NTHREADS = 384;

__device__ __align__(1024) uint8_t g_wqkv[8 * 10 * 30720];
__device__ __align__(1024) uint8_t g_win[8 * 10 * 24576];
__device__ __align__(1024) uint8_t g_wo[8 * 10 * 10240];
__device__ __align__(1024) uint8_t g_wout[8 * 12 * 10240];
__device__ __align__(128) float g_csq[10 * 8 * 240];
__device__ __align__(128) float g_csi[10 * 8 * 192];
__device__ __align__(128) __nv_bfloat16 g_x[3 * S_ * D_];
__device__ __align__(128) __nv_bfloat16 g_o[S_ * D_];
__device__ __align__(128) __nv_bfloat16 g_u[S_ * FH_];
__device__ __align__(128) __nv_bfloat16 g_zt[FH_ * S_];
__device__ __align__(128) float g_kv[2 * 8 * 3840];
__device__ __align__(128) uint4 g_xstat[16 * 8 * 128];
__device__ __align__(128) uint4 g_zstat[16 * 8 * 128];
__device__ __align__(128) uint32_t g_flags[256 * 32];

constexpr int F_CNT = 0, F_KV = 1, F_O = 17, F_X1 = 49, F_ZS = 81, F_U = 113, F_X2 = 145, F_ZN = 161,
              F_WQ = 177, F_WREST = 185;

constexpr uint32_t SM_XT = 200 * 1024;
constexpr uint32_t SM_SMALL = SM_XT + 20480;
constexpr uint32_t SM_BARS = SM_SMALL;
constexpr uint32_t SM_CSQ = SM_SMALL + 256;
constexpr uint32_t SM_CSI = SM_SMALL + 1280;
constexpr uint32_t SM_ROWSTAT = SM_SMALL + 2048;
constexpr uint32_t SM_BSP = SM_SMALL + 4096;
constexpr uint32_t SM_ZMASK = SM_SMALL + 4608;
constexpr uint32_t SMEM_BYTES = 232448;

constexpr uint32_t B_FULL = 0, B_EMPTY = 64, B_MMADONE = 128, B_BFULL = 136, B_XT = 144, B_RAW0 = 152, B_XSFULL = 160,
                   B_STGFREE = 168, B_RAW1 = 176, B_STGO = 184  , B_P0A = 200, B_P0B = 208, B_PHI = 216, B_BFULL1 = 224;

constexpr uint32_t SM_PHI = 0, PHI_HEAD = 12320;
constexpr uint32_t SM_VST = 49408, VST_HEAD = 6176;
constexpr uint32_t SM_KVS = 74240;
constexpr uint32_t SM_KVB = 89600, KVB_HEAD = 2304;
constexpr uint32_t SM_OST = 49408;
constexpr uint32_t SM_WO = 100 * 1024;
constexpr uint32_t SM_ZT0 = 5 * 28672 + 16384, SM_ZT1 = 6 * 28672 + 16384;
constexpr uint32_t SM_UST = 0;

struct Params {
  CUtensorMap tmAx64, tmAx80, tmX64, tmX80, tmOut80, tmO64, tmO80, tmU64, tmUs64, tmUs32, tmZ, tmWsp, tmWq, tmWo, tmWi, tmWout;
  const __nv_bfloat16 *wphi, *wsp, *bsp;
};

__device__ __forceinline__ uint32_t smem_u32(const void* p) { return (uint32_t)__cvta_generic_to_shared(p); }
__device__ __forceinline__ void mbar_init(uint32_t bar, uint32_t cnt) { asm volatile("mbarrier.init.shared::cta.b64 [%0], %1;" ::"r"(bar), "r"(cnt)); }
__device__ __forceinline__ void mbar_expect_tx(uint32_t bar, uint32_t bytes) { asm volatile("mbarrier.arrive.expect_tx.shared::cta.b64 _, [%0], %1;" ::"r"(bar), "r"(bytes) : "memory"); }
__device__ __forceinline__ void mbar_arrive(uint32_t bar) { asm volatile("mbarrier.arrive.shared::cta.b64 _, [%0];" ::"r"(bar) : "memory"); }
__device__ __forceinline__ void mbar_arrive_remote(uint32_t cluster_addr) { asm volatile("mbarrier.arrive.shared::cluster.b64 _, [%0];" ::"r"(cluster_addr) : "memory"); }
__device__ __forceinline__ uint32_t mapa(uint32_t a, uint32_t cta) { uint32_t r; asm volatile("mapa.shared::cluster.u32 %0, %1, %2;" : "=r"(r) : "r"(a), "r"(cta)); return r; }
constexpr uint32_t SPIN_LIMIT = 1u << 22;
__device__ __forceinline__ void mbar_wait(uint32_t bar, uint32_t parity) {
  asm volatile(
      "{\n.reg .pred p, t;\n.reg .u32 c;\nmov.u32 c, 0;\n"
      "MW_%=:\nmbarrier.try_wait.parity.shared::cta.b64 p, [%0], %1;\n@p bra MD_%=;\n"
      "add.u32 c, c, 1;\nsetp.gt.u32 t, c, %2;\n@t trap;\nbra MW_%=;\nMD_%=:\n}"
      ::"r"(bar), "r"(parity), "n"(SPIN_LIMIT) : "memory");
}
__device__ __forceinline__ uint32_t ld_acquire(const uint32_t* p) { uint32_t v; asm volatile("ld.acquire.gpu.global.u32 %0, [%1];" : "=r"(v) : "l"(p) : "memory"); return v; }
__device__ __forceinline__ void signal_flag(uint32_t* p) {
  asm volatile("fence.proxy.async.global;\nred.release.gpu.global.add.u32 [%0], 1;" ::"l"(p) : "memory");
}
__device__ __forceinline__ void wait_flag(const uint32_t* p, uint32_t target) {
  asm volatile(
      "{\n.reg .pred p, t;\n.reg .u32 c, v;\nmov.u32 c, 0;\n"
      "FW_%=:\nld.acquire.gpu.global.u32 v, [%0];\nsub.u32 v, v, %1;\nsetp.ge.s32 p, v, 0;\n@p bra FD_%=;\n"
      "add.u32 c, c, 1;\nsetp.gt.u32 t, c, %2;\n@t trap;\nbra FW_%=;\nFD_%=:\nfence.proxy.async.global;\n}"
      ::"l"(p), "r"(target), "n"(SPIN_LIMIT) : "memory");
}
__device__ __forceinline__ uint32_t wait_smem_bit(uint32_t addr, uint32_t bit) {
  uint32_t v;
  asm volatile(
      "{\n.reg .pred p, t;\n.reg .u32 c, m;\nmov.u32 c, 0;\n"
      "BW_%=:\nld.volatile.shared.u32 %0, [%1];\nshr.u32 m, %0, %2;\nand.b32 m, m, 1;\nsetp.ne.u32 p, m, 0;\n@p bra BD_%=;\n"
      "add.u32 c, c, 1;\nsetp.gt.u32 t, c, %3;\n@t trap;\nbra BW_%=;\nBD_%=:\n}"
      : "=r"(v) : "r"(addr), "r"(bit), "n"(SPIN_LIMIT * 8) : "memory");
  return v;
}
__device__ __forceinline__ bool elect_one() {
  uint32_t p;
  asm volatile("{\n.reg .pred P;\nelect.sync _|P, 0xffffffff;\nselp.u32 %0, 1, 0, P;\n}" : "=r"(p));
  return p;
}
__device__ __forceinline__ void trap_if(bool c) { asm volatile("{\n.reg .pred t;\nsetp.ne.u32 t, %0, 0;\n@t trap;\n}" ::"r"((uint32_t)c)); }
__device__ __forceinline__ void st_tagged(uint4* p, float a, float b, uint32_t tag) {
  const uint64_t w0 = ((uint64_t)tag << 32) | __float_as_uint(a), w1 = ((uint64_t)tag << 32) | __float_as_uint(b);
  asm volatile("st.relaxed.gpu.global.v2.b64 [%0], {%1, %2};" ::"l"(p), "l"(w0), "l"(w1) : "memory");
}
__device__ __forceinline__ bool ld_tagged(const uint4* p, uint32_t tag, float2& v) {
  uint64_t w0, w1;
  asm volatile("ld.relaxed.gpu.global.v2.b64 {%0, %1}, [%2];" : "=l"(w0), "=l"(w1) : "l"(p) : "memory");
  v.x = __uint_as_float((uint32_t)w0); v.y = __uint_as_float((uint32_t)w1);
  return (uint32_t)(w0 >> 32) == tag && (uint32_t)(w1 >> 32) == tag;
}
__device__ __forceinline__ float ld_cg_f(const float* p) { float v; asm volatile("ld.relaxed.gpu.global.f32 %0, [%1];" : "=f"(v) : "l"(p) : "memory"); return v; }
__device__ __forceinline__ float4 ld_cg_f4(const float* p) {
  float4 v; asm volatile("ld.global.cg.v4.f32 {%0, %1, %2, %3}, [%4];" : "=f"(v.x), "=f"(v.y), "=f"(v.z), "=f"(v.w) : "l"(p) : "memory"); return v;
}
__device__ __forceinline__ void tma_ld(uint32_t dst, const CUtensorMap* tm, int c0, int c1, uint32_t bar) {
  asm volatile("cp.async.bulk.tensor.2d.shared::cluster.global.mbarrier::complete_tx::bytes [%0], [%1, {%3, %4}], [%2];"
               ::"r"(dst), "l"(tm), "r"(bar), "r"(c0), "r"(c1) : "memory");
}
__device__ __forceinline__ void tma_ld_mc(uint32_t dst, const CUtensorMap* tm, int c0, int c1, uint32_t bar) {
  asm volatile("cp.async.bulk.tensor.2d.shared::cluster.global.mbarrier::complete_tx::bytes.multicast::cluster [%0], [%1, {%3, %4}], [%2], %5;"
               ::"r"(dst), "l"(tm), "r"(bar), "r"(c0), "r"(c1), "h"((uint16_t)3) : "memory");
}
__device__ __forceinline__ void tma_st(const CUtensorMap* tm, uint32_t src, int c0, int c1) {
  asm volatile("cp.async.bulk.tensor.2d.global.shared::cta.bulk_group [%0, {%2, %3}], [%1];" ::"l"(tm), "r"(src), "r"(c0), "r"(c1) : "memory");
}
__device__ __forceinline__ void bulk_ld(uint32_t dst, const void* src, uint32_t bytes, uint32_t bar) {
  asm volatile("cp.async.bulk.shared::cluster.global.mbarrier::complete_tx::bytes [%0], [%1], %2, [%3];" ::"r"(dst), "l"(src), "r"(bytes), "r"(bar) : "memory");
}
__device__ __forceinline__ void bulk_st(void* dst, uint32_t src, uint32_t bytes) {
  asm volatile("cp.async.bulk.global.shared::cta.bulk_group [%0], [%1], %2;" ::"l"(dst), "r"(src), "r"(bytes) : "memory");
}
__device__ __forceinline__ void bulk_red_f32(void* dst, uint32_t src, uint32_t bytes) {
  asm volatile("cp.reduce.async.bulk.global.shared::cta.bulk_group.add.f32 [%0], [%1], %2;" ::"l"(dst), "r"(src), "r"(bytes) : "memory");
}
__device__ __forceinline__ void bulk_commit() { asm volatile("cp.async.bulk.commit_group;" ::: "memory"); }
__device__ __forceinline__ void bulk_wait_all() { asm volatile("cp.async.bulk.wait_group 0;" ::: "memory"); }
__device__ __forceinline__ void bulk_wait_read() { asm volatile("cp.async.bulk.wait_group.read 0;" ::: "memory"); }
__device__ __forceinline__ void fence_async_global() { asm volatile("fence.proxy.async.global;" ::: "memory"); }
__device__ __forceinline__ void fence_async_smem() { asm volatile("fence.proxy.async.shared::cta;" ::: "memory"); }
__device__ __forceinline__ void bar_sync(int id, int n) { asm volatile("bar.sync %0, %1;" ::"r"(id), "r"(n) : "memory"); }
__device__ __forceinline__ void wgmma_fence() { asm volatile("wgmma.fence.sync.aligned;" ::: "memory"); }
__device__ __forceinline__ void wgmma_commit() { asm volatile("wgmma.commit_group.sync.aligned;" ::: "memory"); }
template <int N> __device__ __forceinline__ void wgmma_wait() { asm volatile("wgmma.wait_group.sync.aligned %0;" ::"n"(N) : "memory"); }
__device__ __forceinline__ uint64_t make_desc(uint32_t addr, uint32_t lbo, uint32_t sbo, uint32_t mode) {
  return (uint64_t)((addr & 0x3FFFF) >> 4) | ((uint64_t)(lbo >> 4) << 16) | ((uint64_t)(sbo >> 4) << 32) | ((uint64_t)mode << 62);
}
__device__ __forceinline__ uint64_t desc_k128(uint32_t addr) { return make_desc(addr, 16, 1024, 1); }
__device__ __forceinline__ uint32_t pack_bf16(float lo, float hi) { uint32_t r; asm("cvt.rn.bf16x2.f32 %0, %1, %2;" : "=r"(r) : "f"(hi), "f"(lo)); return r; }
__device__ __forceinline__ float bf_lo(uint32_t v) { return __uint_as_float(v << 16); }
__device__ __forceinline__ float bf_hi(uint32_t v) { return __uint_as_float(v & 0xffff0000u); }
__device__ __forceinline__ float ex2(float x) { float y; asm("ex2.approx.ftz.f32 %0, %1;" : "=f"(y) : "f"(x)); return y; }
__device__ __forceinline__ float rcp(float x) { float y; asm("rcp.approx.ftz.f32 %0, %1;" : "=f"(y) : "f"(x)); return y; }
__device__ __forceinline__ float tanh_fast(float x) { float y; asm("tanh.approx.f32 %0, %1;" : "=f"(y) : "f"(x)); return y; }
__device__ __forceinline__ void sts32(uint32_t a, uint32_t v) { asm volatile("st.shared.u32 [%0], %1;" ::"r"(a), "r"(v) : "memory"); }
__device__ __forceinline__ void sts64f(uint32_t a, float x, float y) { asm volatile("st.shared.v2.f32 [%0], {%1, %2};" ::"r"(a), "f"(x), "f"(y) : "memory"); }
__device__ __forceinline__ void sts128(uint32_t a, uint32_t x, uint32_t y, uint32_t z, uint32_t w) {
  asm volatile("st.shared.v4.u32 [%0], {%1, %2, %3, %4};" ::"r"(a), "r"(x), "r"(y), "r"(z), "r"(w) : "memory");
}
__device__ __forceinline__ uint32_t lds32(uint32_t a) { uint32_t v; asm volatile("ld.shared.u32 %0, [%1];" : "=r"(v) : "r"(a) : "memory"); return v; }
__device__ __forceinline__ float lds32f(uint32_t a) { float v; asm volatile("ld.shared.f32 %0, [%1];" : "=f"(v) : "r"(a) : "memory"); return v; }
__device__ __forceinline__ float2 lds64f(uint32_t a) { float2 v; asm volatile("ld.shared.v2.f32 {%0, %1}, [%2];" : "=f"(v.x), "=f"(v.y) : "r"(a) : "memory"); return v; }
__device__ __forceinline__ float4 lds128f(uint32_t a) { float4 v; asm volatile("ld.shared.v4.f32 {%0, %1, %2, %3}, [%4];" : "=f"(v.x), "=f"(v.y), "=f"(v.z), "=f"(v.w) : "r"(a) : "memory"); return v; }
__device__ __forceinline__ void ldsm4(uint32_t a, uint32_t& r0, uint32_t& r1, uint32_t& r2, uint32_t& r3) {
  asm volatile("ldmatrix.sync.aligned.m8n8.x4.shared.b16 {%0, %1, %2, %3}, [%4];" : "=r"(r0), "=r"(r1), "=r"(r2), "=r"(r3) : "r"(a) : "memory");
}
__device__ __forceinline__ void ldsm4t(uint32_t a, uint32_t& r0, uint32_t& r1, uint32_t& r2, uint32_t& r3) {
  asm volatile("ldmatrix.sync.aligned.m8n8.x4.trans.shared.b16 {%0, %1, %2, %3}, [%4];" : "=r"(r0), "=r"(r1), "=r"(r2), "=r"(r3) : "r"(a) : "memory");
}
__device__ __forceinline__ void stsm4(uint32_t a, uint32_t r0, uint32_t r1, uint32_t r2, uint32_t r3) {
  asm volatile("stmatrix.sync.aligned.m8n8.x4.shared.b16 [%0], {%1, %2, %3, %4};" ::"r"(a), "r"(r0), "r"(r1), "r"(r2), "r"(r3) : "memory");
}
__device__ __forceinline__ void stsm4t(uint32_t a, uint32_t r0, uint32_t r1, uint32_t r2, uint32_t r3) {
  asm volatile("stmatrix.sync.aligned.m8n8.x4.trans.shared.b16 [%0], {%1, %2, %3, %4};" ::"r"(a), "r"(r0), "r"(r1), "r"(r2), "r"(r3) : "memory");
}
__device__ __forceinline__ void mma16816(float (&d)[4], uint32_t a0, uint32_t a1, uint32_t a2, uint32_t a3, uint32_t b0, uint32_t b1) {
  asm volatile("mma.sync.aligned.m16n8k16.row.col.f32.bf16.bf16.f32 {%0, %1, %2, %3}, {%4, %5, %6, %7}, {%8, %9}, {%0, %1, %2, %3};"
               : "+f"(d[0]), "+f"(d[1]), "+f"(d[2]), "+f"(d[3]) : "r"(a0), "r"(a1), "r"(a2), "r"(a3), "r"(b0), "r"(b1));
}
__device__ __forceinline__ void prefetch_l2_bulk(const void* p, uint32_t bytes) { asm volatile("cp.async.bulk.prefetch.L2.global [%0], %1;" ::"l"(p), "r"(bytes) : "memory"); }
#define TS(slot)
#define TSP(slot)

template <int TA, int TB> __device__ __forceinline__ void wgmma_ss_n24(float (&d)[12], uint64_t da, uint64_t db, int sd) {
  asm volatile("{\n.reg .pred p;\n"
    "setp.ne.b32 p, %14, 0;\n"
    "wgmma.mma_async.sync.aligned.m64n24k16.f32.bf16.bf16 "
    "{%0, %1, %2, %3, %4, %5, %6, %7, %8, %9, %10, %11}, "
    "%12, %13, p, 1, 1, %15, %16;\n}\n"
    : "+f"(d[0]), "+f"(d[1]), "+f"(d[2]), "+f"(d[3]), "+f"(d[4]), "+f"(d[5]), "+f"(d[6]), "+f"(d[7]),
      "+f"(d[8]), "+f"(d[9]), "+f"(d[10]), "+f"(d[11])
    : "l"(da), "l"(db), "r"(sd), "n"(TA), "n"(TB));
}
template <int TA, int TB> __device__ __forceinline__ void wgmma_ss_n40(float (&d)[20], uint64_t da, uint64_t db, int sd) {
  asm volatile("{\n.reg .pred p;\n"
    "setp.ne.b32 p, %22, 0;\n"
    "wgmma.mma_async.sync.aligned.m64n40k16.f32.bf16.bf16 "
    "{%0, %1, %2, %3, %4, %5, %6, %7, %8, %9, %10, %11, %12, %13, %14, %15, "
    "%16, %17, %18, %19}, "
    "%20, %21, p, 1, 1, %23, %24;\n}\n"
    : "+f"(d[0]), "+f"(d[1]), "+f"(d[2]), "+f"(d[3]), "+f"(d[4]), "+f"(d[5]), "+f"(d[6]), "+f"(d[7]),
      "+f"(d[8]), "+f"(d[9]), "+f"(d[10]), "+f"(d[11]), "+f"(d[12]), "+f"(d[13]), "+f"(d[14]), "+f"(d[15]),
      "+f"(d[16]), "+f"(d[17]), "+f"(d[18]), "+f"(d[19])
    : "l"(da), "l"(db), "r"(sd), "n"(TA), "n"(TB));
}
template <int TA, int TB> __device__ __forceinline__ void wgmma_ss_n80(float (&d)[40], uint64_t da, uint64_t db, int sd) {
  asm volatile("{\n.reg .pred p;\n"
    "setp.ne.b32 p, %42, 0;\n"
    "wgmma.mma_async.sync.aligned.m64n80k16.f32.bf16.bf16 "
    "{%0, %1, %2, %3, %4, %5, %6, %7, %8, %9, %10, %11, %12, %13, %14, %15, "
    "%16, %17, %18, %19, %20, %21, %22, %23, %24, %25, %26, %27, %28, %29, %30, %31, "
    "%32, %33, %34, %35, %36, %37, %38, %39}, "
    "%40, %41, p, 1, 1, %43, %44;\n}\n"
    : "+f"(d[0]), "+f"(d[1]), "+f"(d[2]), "+f"(d[3]), "+f"(d[4]), "+f"(d[5]), "+f"(d[6]), "+f"(d[7]),
      "+f"(d[8]), "+f"(d[9]), "+f"(d[10]), "+f"(d[11]), "+f"(d[12]), "+f"(d[13]), "+f"(d[14]), "+f"(d[15]),
      "+f"(d[16]), "+f"(d[17]), "+f"(d[18]), "+f"(d[19]), "+f"(d[20]), "+f"(d[21]), "+f"(d[22]), "+f"(d[23]),
      "+f"(d[24]), "+f"(d[25]), "+f"(d[26]), "+f"(d[27]), "+f"(d[28]), "+f"(d[29]), "+f"(d[30]), "+f"(d[31]),
      "+f"(d[32]), "+f"(d[33]), "+f"(d[34]), "+f"(d[35]), "+f"(d[36]), "+f"(d[37]), "+f"(d[38]), "+f"(d[39])
    : "l"(da), "l"(db), "r"(sd), "n"(TA), "n"(TB));
}
template <int TA, int TB> __device__ __forceinline__ void wgmma_ss_n96(float (&d)[48], uint64_t da, uint64_t db, int sd) {
  asm volatile("{\n.reg .pred p;\n"
    "setp.ne.b32 p, %50, 0;\n"
    "wgmma.mma_async.sync.aligned.m64n96k16.f32.bf16.bf16 "
    "{%0, %1, %2, %3, %4, %5, %6, %7, %8, %9, %10, %11, %12, %13, %14, %15, "
    "%16, %17, %18, %19, %20, %21, %22, %23, %24, %25, %26, %27, %28, %29, %30, %31, "
    "%32, %33, %34, %35, %36, %37, %38, %39, %40, %41, %42, %43, %44, %45, %46, %47}, "
    "%48, %49, p, 1, 1, %51, %52;\n}\n"
    : "+f"(d[0]), "+f"(d[1]), "+f"(d[2]), "+f"(d[3]), "+f"(d[4]), "+f"(d[5]), "+f"(d[6]), "+f"(d[7]),
      "+f"(d[8]), "+f"(d[9]), "+f"(d[10]), "+f"(d[11]), "+f"(d[12]), "+f"(d[13]), "+f"(d[14]), "+f"(d[15]),
      "+f"(d[16]), "+f"(d[17]), "+f"(d[18]), "+f"(d[19]), "+f"(d[20]), "+f"(d[21]), "+f"(d[22]), "+f"(d[23]),
      "+f"(d[24]), "+f"(d[25]), "+f"(d[26]), "+f"(d[27]), "+f"(d[28]), "+f"(d[29]), "+f"(d[30]), "+f"(d[31]),
      "+f"(d[32]), "+f"(d[33]), "+f"(d[34]), "+f"(d[35]), "+f"(d[36]), "+f"(d[37]), "+f"(d[38]), "+f"(d[39]),
      "+f"(d[40]), "+f"(d[41]), "+f"(d[42]), "+f"(d[43]), "+f"(d[44]), "+f"(d[45]), "+f"(d[46]), "+f"(d[47])
    : "l"(da), "l"(db), "r"(sd), "n"(TA), "n"(TB));
}
template <int TA, int TB> __device__ __forceinline__ void wgmma_ss_n192(float (&d)[96], uint64_t da, uint64_t db, int sd) {
  asm volatile("{\n.reg .pred p;\n"
    "setp.ne.b32 p, %98, 0;\n"
    "wgmma.mma_async.sync.aligned.m64n192k16.f32.bf16.bf16 "
    "{%0, %1, %2, %3, %4, %5, %6, %7, %8, %9, %10, %11, %12, %13, %14, %15, "
    "%16, %17, %18, %19, %20, %21, %22, %23, %24, %25, %26, %27, %28, %29, %30, %31, "
    "%32, %33, %34, %35, %36, %37, %38, %39, %40, %41, %42, %43, %44, %45, %46, %47, "
    "%48, %49, %50, %51, %52, %53, %54, %55, %56, %57, %58, %59, %60, %61, %62, %63, "
    "%64, %65, %66, %67, %68, %69, %70, %71, %72, %73, %74, %75, %76, %77, %78, %79, "
    "%80, %81, %82, %83, %84, %85, %86, %87, %88, %89, %90, %91, %92, %93, %94, %95}, "
    "%96, %97, p, 1, 1, %99, %100;\n}\n"
    : "+f"(d[0]), "+f"(d[1]), "+f"(d[2]), "+f"(d[3]), "+f"(d[4]), "+f"(d[5]), "+f"(d[6]), "+f"(d[7]),
      "+f"(d[8]), "+f"(d[9]), "+f"(d[10]), "+f"(d[11]), "+f"(d[12]), "+f"(d[13]), "+f"(d[14]), "+f"(d[15]),
      "+f"(d[16]), "+f"(d[17]), "+f"(d[18]), "+f"(d[19]), "+f"(d[20]), "+f"(d[21]), "+f"(d[22]), "+f"(d[23]),
      "+f"(d[24]), "+f"(d[25]), "+f"(d[26]), "+f"(d[27]), "+f"(d[28]), "+f"(d[29]), "+f"(d[30]), "+f"(d[31]),
      "+f"(d[32]), "+f"(d[33]), "+f"(d[34]), "+f"(d[35]), "+f"(d[36]), "+f"(d[37]), "+f"(d[38]), "+f"(d[39]),
      "+f"(d[40]), "+f"(d[41]), "+f"(d[42]), "+f"(d[43]), "+f"(d[44]), "+f"(d[45]), "+f"(d[46]), "+f"(d[47]),
      "+f"(d[48]), "+f"(d[49]), "+f"(d[50]), "+f"(d[51]), "+f"(d[52]), "+f"(d[53]), "+f"(d[54]), "+f"(d[55]),
      "+f"(d[56]), "+f"(d[57]), "+f"(d[58]), "+f"(d[59]), "+f"(d[60]), "+f"(d[61]), "+f"(d[62]), "+f"(d[63]),
      "+f"(d[64]), "+f"(d[65]), "+f"(d[66]), "+f"(d[67]), "+f"(d[68]), "+f"(d[69]), "+f"(d[70]), "+f"(d[71]),
      "+f"(d[72]), "+f"(d[73]), "+f"(d[74]), "+f"(d[75]), "+f"(d[76]), "+f"(d[77]), "+f"(d[78]), "+f"(d[79]),
      "+f"(d[80]), "+f"(d[81]), "+f"(d[82]), "+f"(d[83]), "+f"(d[84]), "+f"(d[85]), "+f"(d[86]), "+f"(d[87]),
      "+f"(d[88]), "+f"(d[89]), "+f"(d[90]), "+f"(d[91]), "+f"(d[92]), "+f"(d[93]), "+f"(d[94]), "+f"(d[95])
    : "l"(da), "l"(db), "r"(sd), "n"(TA), "n"(TB));
}
template <int TA, int TB> __device__ __forceinline__ void wgmma_ss_n240(float (&d)[120], uint64_t da, uint64_t db, int sd) {
  asm volatile("{\n.reg .pred p;\n"
    "setp.ne.b32 p, %122, 0;\n"
    "wgmma.mma_async.sync.aligned.m64n240k16.f32.bf16.bf16 "
    "{%0, %1, %2, %3, %4, %5, %6, %7, %8, %9, %10, %11, %12, %13, %14, %15, "
    "%16, %17, %18, %19, %20, %21, %22, %23, %24, %25, %26, %27, %28, %29, %30, %31, "
    "%32, %33, %34, %35, %36, %37, %38, %39, %40, %41, %42, %43, %44, %45, %46, %47, "
    "%48, %49, %50, %51, %52, %53, %54, %55, %56, %57, %58, %59, %60, %61, %62, %63, "
    "%64, %65, %66, %67, %68, %69, %70, %71, %72, %73, %74, %75, %76, %77, %78, %79, "
    "%80, %81, %82, %83, %84, %85, %86, %87, %88, %89, %90, %91, %92, %93, %94, %95, "
    "%96, %97, %98, %99, %100, %101, %102, %103, %104, %105, %106, %107, %108, %109, %110, %111, "
    "%112, %113, %114, %115, %116, %117, %118, %119}, "
    "%120, %121, p, 1, 1, %123, %124;\n}\n"
    : "+f"(d[0]), "+f"(d[1]), "+f"(d[2]), "+f"(d[3]), "+f"(d[4]), "+f"(d[5]), "+f"(d[6]), "+f"(d[7]),
      "+f"(d[8]), "+f"(d[9]), "+f"(d[10]), "+f"(d[11]), "+f"(d[12]), "+f"(d[13]), "+f"(d[14]), "+f"(d[15]),
      "+f"(d[16]), "+f"(d[17]), "+f"(d[18]), "+f"(d[19]), "+f"(d[20]), "+f"(d[21]), "+f"(d[22]), "+f"(d[23]),
      "+f"(d[24]), "+f"(d[25]), "+f"(d[26]), "+f"(d[27]), "+f"(d[28]), "+f"(d[29]), "+f"(d[30]), "+f"(d[31]),
      "+f"(d[32]), "+f"(d[33]), "+f"(d[34]), "+f"(d[35]), "+f"(d[36]), "+f"(d[37]), "+f"(d[38]), "+f"(d[39]),
      "+f"(d[40]), "+f"(d[41]), "+f"(d[42]), "+f"(d[43]), "+f"(d[44]), "+f"(d[45]), "+f"(d[46]), "+f"(d[47]),
      "+f"(d[48]), "+f"(d[49]), "+f"(d[50]), "+f"(d[51]), "+f"(d[52]), "+f"(d[53]), "+f"(d[54]), "+f"(d[55]),
      "+f"(d[56]), "+f"(d[57]), "+f"(d[58]), "+f"(d[59]), "+f"(d[60]), "+f"(d[61]), "+f"(d[62]), "+f"(d[63]),
      "+f"(d[64]), "+f"(d[65]), "+f"(d[66]), "+f"(d[67]), "+f"(d[68]), "+f"(d[69]), "+f"(d[70]), "+f"(d[71]),
      "+f"(d[72]), "+f"(d[73]), "+f"(d[74]), "+f"(d[75]), "+f"(d[76]), "+f"(d[77]), "+f"(d[78]), "+f"(d[79]),
      "+f"(d[80]), "+f"(d[81]), "+f"(d[82]), "+f"(d[83]), "+f"(d[84]), "+f"(d[85]), "+f"(d[86]), "+f"(d[87]),
      "+f"(d[88]), "+f"(d[89]), "+f"(d[90]), "+f"(d[91]), "+f"(d[92]), "+f"(d[93]), "+f"(d[94]), "+f"(d[95]),
      "+f"(d[96]), "+f"(d[97]), "+f"(d[98]), "+f"(d[99]), "+f"(d[100]), "+f"(d[101]), "+f"(d[102]), "+f"(d[103]),
      "+f"(d[104]), "+f"(d[105]), "+f"(d[106]), "+f"(d[107]), "+f"(d[108]), "+f"(d[109]), "+f"(d[110]), "+f"(d[111]),
      "+f"(d[112]), "+f"(d[113]), "+f"(d[114]), "+f"(d[115]), "+f"(d[116]), "+f"(d[117]), "+f"(d[118]), "+f"(d[119])
    : "l"(da), "l"(db), "r"(sd), "n"(TA), "n"(TB));
}

template <int N> __device__ __forceinline__ void fence_regs(float (&a)[N]) {
#pragma unroll
  for (int i = 0; i < N; i++) asm volatile("" : "+f"(a[i])::"memory");
}
template <int N> struct WG;
template <> struct WG<240> { static __device__ __forceinline__ void mma(float (&d)[120], uint64_t a, uint64_t b, int sd) { wgmma_ss_n240<0, 0>(d, a, b, sd); } };
template <> struct WG<192> { static __device__ __forceinline__ void mma(float (&d)[96], uint64_t a, uint64_t b, int sd) { wgmma_ss_n192<0, 0>(d, a, b, sd); } };
template <> struct WG<96> { static __device__ __forceinline__ void mma(float (&d)[48], uint64_t a, uint64_t b, int sd) { wgmma_ss_n96<0, 0>(d, a, b, sd); } };
template <> struct WG<80> { static __device__ __forceinline__ void mma(float (&d)[40], uint64_t a, uint64_t b, int sd) { wgmma_ss_n80<0, 0>(d, a, b, sd); } };

template <int BN, int SLOTS, uint32_t SLOTB, int KB, bool BRES>
__device__ __forceinline__ void mainloop(float (&acc)[BN / 2], int nit, uint32_t sb, uint32_t boff, int wg, bool elect, uint32_t& ph, uint32_t peer_bars, int tsslot,
                                         uint32_t pbf = 0) {
  const uint32_t bars = sb + SM_BARS;
  const uint64_t da0 = desc_k128(sb + wg * 8192), db0 = desc_k128(sb + boff);
  int s = 0, sp = 0;
#pragma unroll
  for (int i = 0; i < BN / 2; i++) acc[i] = 0.f;
  fence_regs(acc);
#pragma unroll 1
  for (int it = 0; it < nit; it++) {
    if (BRES && (it & ~2) == 0) mbar_wait(bars + (it == 0 ? B_BFULL : B_BFULL1), pbf);
    mbar_wait(bars + B_FULL + 8 * s, (ph >> s) & 1);
    ph ^= 1u << s;
    if (it == 0) TS(tsslot);
    const uint64_t da = da0 + (uint64_t)(s * (SLOTB >> 4));
    const uint64_t db = BRES ? db0 + (uint64_t)((it < 5 ? it : it - 5) * (KB * 10240 >> 4)) : db0 + (uint64_t)(s * (SLOTB >> 4));
    wgmma_fence();
#pragma unroll
    for (int g = 0; g < KB; g++)
#pragma unroll
      for (int k = 0; k < 4; k++) WG<BN>::mma(acc, da + g * (16384 >> 4) + 2 * k, db + g * (10240 >> 4) + 2 * k, 1);
    wgmma_commit();
    wgmma_wait<1>();
    if (it > 0 && elect) {
      mbar_arrive(bars + B_EMPTY + 8 * sp);
      if (USE_MC) mbar_arrive_remote(peer_bars + B_EMPTY + 8 * sp);
    }
    sp = s;
    s = (s + 1 == SLOTS) ? 0 : s + 1;
  }
  wgmma_wait<0>();
  fence_regs(acc);
  if (elect) {
    mbar_arrive(bars + B_EMPTY + 8 * sp);
    mbar_arrive(bars + B_MMADONE);
    if (USE_MC) { mbar_arrive_remote(peer_bars + B_EMPTY + 8 * sp); mbar_arrive_remote(peer_bars + B_MMADONE); }
  }
}

__device__ __forceinline__ void load_a(uint32_t dst, const CUtensorMap* tm, int col, int row0, uint32_t rank, uint32_t bar) {
  if (USE_MC) tma_ld_mc(dst + rank * 8192, tm, col, row0 + rank * 64, bar);
  else { tma_ld(dst, tm, col, row0, bar); tma_ld(dst + 8192, tm, col, row0 + 64, bar); }
}

template <int NV>
__device__ __forceinline__ void row_partial_stats(const float (&v)[NV], float inv_n, float& mean, float& m2) {
  float s0 = 0.f, s1 = 0.f, s2 = 0.f, s3 = 0.f;
#pragma unroll
  for (int i = 0; i < NV; i += 4) { s0 += v[i]; s1 += v[i + 1]; s2 += v[i + 2]; s3 += v[i + 3]; }
  float s = (s0 + s1) + (s2 + s3);
  s += __shfl_xor_sync(0xffffffffu, s, 1);
  s += __shfl_xor_sync(0xffffffffu, s, 2);
  mean = s * inv_n;
  float q0 = 0.f, q1 = 0.f, q2 = 0.f, q3 = 0.f;
#pragma unroll
  for (int i = 0; i < NV; i += 4) {
    const float d0 = v[i] - mean, d1 = v[i + 1] - mean, d2 = v[i + 2] - mean, d3 = v[i + 3] - mean;
    q0 = fmaf(d0, d0, q0); q1 = fmaf(d1, d1, q1); q2 = fmaf(d2, d2, q2); q3 = fmaf(d3, d3, q3);
  }
  float q = (q0 + q1) + (q2 + q3);
  q += __shfl_xor_sync(0xffffffffu, q, 1);
  q += __shfl_xor_sync(0xffffffffu, q, 2);
  m2 = q;
}

template <int NB, int NW, bool CS>
__device__ __forceinline__ void transpose_item(uint32_t raw, uint32_t img, int row0, uint32_t cs, int warp, int lane) {
#pragma unroll 1
  for (int nb = warp; nb < NB / 8; nb += NW) {
    float sum = 0.f;
#pragma unroll
    for (int t = 0; t < 2; t++) {
      uint32_t r0, r1, r2, r3;
      ldsm4t(raw + (8 * (4 * t + (lane >> 3)) + (lane & 7)) * (2 * NB) + nb * 16, r0, r1, r2, r3);
      const int n = row0 + 8 * nb + (lane & 7), c = 4 * t + (lane >> 3);
      stsm4(img + n * 128 + ((c ^ (n & 7)) << 4), r0, r1, r2, r3);
      if (CS) sum += ((bf_lo(r0) + bf_hi(r0)) + (bf_lo(r1) + bf_hi(r1))) + ((bf_lo(r2) + bf_hi(r2)) + (bf_lo(r3) + bf_hi(r3)));
    }
    if (CS) {
      sum += __shfl_xor_sync(0xffffffffu, sum, 1);
      sum += __shfl_xor_sync(0xffffffffu, sum, 2);
      if ((lane & 3) == 0) asm volatile("st.shared.f32 [%0], %1;" ::"r"(cs + (row0 + 8 * nb + (lane >> 2)) * 4), "f"(sum) : "memory");
    }
  }
}

constexpr uint32_t P0_PHIR = 16384, P0_PHIT = 20480, P0_CS = 32768, P0_CS2 = 34816, P0_ZERO = 36864;
constexpr uint32_t P0_RAW0 = 47104 + 16384, P0_IMG0 = 2 * 47104 + 16384;
constexpr uint32_t P0_RAW1 = 3 * 47104, P0_IMG1 = 3 * 47104 + 24576, P0_CS3 = 3 * 47104 + 49152;

__device__ __forceinline__ void prologue_stage0(const Params& p, uint32_t sb, int b, int j, int row0, int tid, int warp, int lane) {
  const uint32_t bars = sb + SM_BARS;
  const bool clsA = b < 80;
  if (clsA) {
    for (int i = tid; i < 5 * 32 * 18; i += NTHREADS) sts32(sb + P0_PHIT + i * 4, 0);
    for (int i = tid; i < 384; i += NTHREADS) sts32(sb + P0_ZERO + i * 4, 0);
    __syncthreads();
    mbar_wait(bars + B_PHI, 0);
#pragma unroll
    for (int it = 0; it < 5; it++) {
      const int i = tid + it * NTHREADS;
      if (i < 1600) {
        const int h = i / 400, d = (i % 400) / 20, e = i % 20;
        uint16_t v;
        asm volatile("ld.shared.u16 %0, [%1];" : "=h"(v) : "r"(sb + P0_PHIR + i * 2) : "memory");
        asm volatile("st.shared.u16 [%0], %1;" ::"r"(sb + P0_PHIT + h * 2304 + e * 72 + d * 2), "h"(v) : "memory");
      } else if (i < 1620) {
        const int e = i - 1600;
        asm volatile("st.shared.u16 [%0], %1;" ::"r"(sb + P0_PHIT + 4 * 2304 + e * 72 + e * 2), "h"((uint16_t)0x3f80) : "memory");
      }
    }
    __syncthreads();
  }
  mbar_wait(bars + B_RAW0, 0);
  TS(114);
  if (warp == 8) {
    if (elect_one()) {
      mbar_expect_tx(bars + B_XT, 20480);
      tma_ld(sb + SM_XT, &p.tmAx80, 80 * j, row0, bars + B_XT);
      if (clsA) {
        mbar_expect_tx(bars + B_RAW1, 20480);
        tma_ld(sb + P0_RAW1, &p.tmWo, 80 * (b / 10), 64 * (b % 10), bars + B_RAW1);
        tma_ld(sb + P0_RAW1 + 10240, &p.tmWout, 80 * (b / 12), 64 * (b % 12), bars + B_RAW1);
      } else if (b < 112) {
        const int i1 = b - 80 + 48, j1 = i1 / 10, k1 = i1 % 10;
        mbar_expect_tx(bars + B_RAW1, 24576);
        tma_ld(sb + P0_RAW1, &p.tmWi, 768 + 96 * j1, 64 * k1, bars + B_RAW1);
        tma_ld(sb + P0_RAW1 + 12288, &p.tmWi, 96 * j1, 64 * k1, bars + B_RAW1);
      } else {
        const int io = 80 + (b - 112);
        mbar_expect_tx(bars + B_RAW1, 10240);
        tma_ld(sb + P0_RAW1, &p.tmWout, 80 * (io / 12), 64 * (io % 12), bars + B_RAW1);
      }
    }
    __syncwarp();
  }
  if (clsA) {
#pragma unroll 1
    for (int hc = warp; hc < 24; hc += 12) {
      const int combo = hc >> 1, khalf = hc & 1, part = combo >> 2, hq = combo & 3;
      const uint32_t pa = sb + P0_PHIT + (part == 2 ? 4 : hq) * 2304;
      const int q = lane & 3, rw = lane >> 2;
      uint32_t a[2][2][4];
#pragma unroll
      for (int mt = 0; mt < 2; mt++)
#pragma unroll
        for (int ks = 0; ks < 2; ks++) {
          const uint32_t base = pa + (16 * mt + rw) * 72 + (16 * ks + 2 * q) * 2;
          a[mt][ks][0] = lds32(base); a[mt][ks][1] = lds32(base + 8 * 72); a[mt][ks][2] = lds32(base + 16); a[mt][ks][3] = lds32(base + 8 * 72 + 16);
        }
      float cs[3] = {0.f, 0.f, 0.f};
#pragma unroll
      for (int nt = 0; nt < 4; nt++) {
        const int krow = 8 * (4 * khalf + nt) + rw;
        const uint32_t rb = sb + P0_RAW0 + part * 10240 + krow * 160 + (20 * hq + 2 * q) * 2;
        const uint32_t b0 = lds32(rb), b1 = lds32(rb + 16), b2 = (q < 2) ? lds32(rb + 32) : 0u;
        float d0[4] = {0.f, 0.f, 0.f, 0.f}, d1[4] = {0.f, 0.f, 0.f, 0.f};
        mma16816(d0, a[0][0][0], a[0][0][1], a[0][0][2], a[0][0][3], b0, b1);
        mma16816(d0, a[0][1][0], a[0][1][1], a[0][1][2], a[0][1][3], b2, 0u);
        mma16816(d1, a[1][0][0], a[1][0][1], a[1][0][2], a[1][0][3], b0, b1);
        mma16816(d1, a[1][1][0], a[1][1][1], a[1][1][2], a[1][1][3], b2, 0u);
        const int kc = 4 * khalf + nt;
        const uint32_t w0 = pack_bf16(d0[0], d0[1]), w1 = pack_bf16(d0[2], d0[3]), w2 = pack_bf16(d1[0], d1[1]);
        {
          const int e = rw, n = 8 * (10 * part + (e >> 1)) + 2 * hq + (e & 1);
          sts32(sb + P0_IMG0 + n * 128 + ((kc ^ (n & 7)) << 4) + q * 4, w0); cs[0] += bf_lo(w0) + bf_hi(w0);
        }
        {
          const int e = rw + 8, n = 8 * (10 * part + (e >> 1)) + 2 * hq + (e & 1);
          sts32(sb + P0_IMG0 + n * 128 + ((kc ^ (n & 7)) << 4) + q * 4, w1); cs[1] += bf_lo(w1) + bf_hi(w1);
        }
        if (rw < 4) {
          const int e = rw + 16, n = 8 * (10 * part + (e >> 1)) + 2 * hq + (e & 1);
          sts32(sb + P0_IMG0 + n * 128 + ((kc ^ (n & 7)) << 4) + q * 4, w2); cs[2] += bf_lo(w2) + bf_hi(w2);
        }
      }
#pragma unroll
      for (int i = 0; i < 3; i++) {
        cs[i] += __shfl_xor_sync(0xffffffffu, cs[i], 1);
        cs[i] += __shfl_xor_sync(0xffffffffu, cs[i], 2);
        const int e = rw + 8 * i;
        if (q == 0 && e < 20) {
          const int n = 8 * (10 * part + (e >> 1)) + 2 * hq + (e & 1);
          asm volatile("st.shared.f32 [%0], %1;" ::"r"(sb + P0_CS + (khalf * 240 + n) * 4), "f"(cs[i]) : "memory");
        }
      }
    }
    __syncthreads();
    if (tid < 240) {
      const float v = lds32f(sb + P0_CS + tid * 4) + lds32f(sb + P0_CS + (240 + tid) * 4);
      asm volatile("st.shared.f32 [%0], %1;" ::"r"(sb + P0_CS2 + tid * 4), "f"(v) : "memory");
    }
  } else {
    transpose_item<96, 12, true>(sb + P0_RAW0, sb + P0_IMG0, 0, sb + P0_CS2, warp, lane);
    transpose_item<96, 12, true>(sb + P0_RAW0 + 12288, sb + P0_IMG0, 96, sb + P0_CS2, warp, lane);
  }
  fence_async_smem();
  __syncthreads();
}

__device__ __forceinline__ void prologue_stage1(uint32_t sb, int b, int warp, int lane, uint4* xstat, uint32_t tag) {
  const uint32_t bars = sb + SM_BARS;
  mbar_wait(bars + B_XT, 0);
#pragma unroll
  for (int h = 0; h < 2; h++) {
    float v[20];
#pragma unroll
    for (int jj = 0; jj < 10; jj++) {
      const uint32_t x = lds32(sb + SM_XT + (16 * warp + 8 * h + (lane >> 2)) * 160 + jj * 16 + (lane & 3) * 4);
      v[2 * jj] = bf_lo(x); v[2 * jj + 1] = bf_hi(x);
    }
    float mean, m2;
    row_partial_stats<20>(v, 1.f / 80.f, mean, m2);
    if ((lane & 3) == 0) st_tagged(xstat + 16 * warp + 8 * h + (lane >> 2), mean, m2, tag);
  }
  mbar_wait(bars + B_RAW1, 0);
  if (b < 80) {
    transpose_item<80, 8, false>(sb + P0_RAW1, sb + P0_IMG1, 0, 0, warp, lane);
    transpose_item<80, 8, false>(sb + P0_RAW1 + 10240, sb + P0_IMG1 + 10240, 0, 0, warp, lane);
  } else if (b < 112) {
    transpose_item<96, 8, true>(sb + P0_RAW1, sb + P0_IMG1, 0, sb + P0_CS3, warp, lane);
    transpose_item<96, 8, true>(sb + P0_RAW1 + 12288, sb + P0_IMG1, 96, sb + P0_CS3, warp, lane);
  } else {
    transpose_item<80, 8, false>(sb + P0_RAW1, sb + P0_IMG1, 0, 0, warp, lane);
  }
  fence_async_smem(); __syncwarp();
  if (lane == 0) mbar_arrive(bars + B_STGO);
}

__device__ __forceinline__ void feature_map(const float (&y)[20], uint32_t (&out)[20]) {
  float mx[4], mn[4];
#pragma unroll
  for (int c = 0; c < 4; c++) { mx[c] = fmaxf(y[c], y[c + 4]); mn[c] = fminf(y[c], y[c + 4]); }
#pragma unroll
  for (int i = 8; i < 20; i++) { mx[i & 3] = fmaxf(mx[i & 3], y[i]); mn[i & 3] = fminf(mn[i & 3], y[i]); }
  const float vmx = fmaxf(fmaxf(mx[0], mx[1]), fmaxf(mx[2], mx[3])), vmn = fminf(fminf(mn[0], mn[1]), fminf(mn[2], mn[3]));
  float ep[20], en[20], sp[4] = {0.f, 0.f, 0.f, 0.f}, sn[4] = {0.f, 0.f, 0.f, 0.f};
#pragma unroll
  for (int i = 0; i < 20; i++) {
    ep[i] = ex2(y[i] - vmx); sp[i & 3] += ep[i];
    en[i] = ex2(vmn - y[i]); sn[i & 3] += en[i];
  }
  const float rp = rcp((sp[0] + sp[1]) + (sp[2] + sp[3])), rn = rcp((sn[0] + sn[1]) + (sn[2] + sn[3]));
#pragma unroll
  for (int i = 0; i < 10; i++) {
    out[i] = pack_bf16(ep[2 * i] * rp, ep[2 * i + 1] * rp);
    out[10 + i] = pack_bf16(en[2 * i] * rn, en[2 * i + 1] * rn);
  }
}

__device__ __forceinline__ void residual_update(const float (&acc)[40], float (&v)[2][20], uint32_t sb, int wg, int w, int lane) {
  const uint32_t rowa = sb + SM_XT + (64 * wg + 16 * w + 8 * ((lane >> 3) & 1) + (lane & 7)) * 160 + (lane >> 4) * 16;
  uint32_t r[5][4];
#pragma unroll
  for (int t = 0; t < 5; t++) ldsm4(rowa + t * 32, r[t][0], r[t][1], r[t][2], r[t][3]);
#pragma unroll
  for (int t = 0; t < 5; t++) {
#pragma unroll
    for (int m = 0; m < 4; m++) {
      const int h = m & 1, jj = 2 * t + (m >> 1);
      r[t][m] = pack_bf16(bf_lo(r[t][m]) + acc[4 * jj + 2 * h], bf_hi(r[t][m]) + acc[4 * jj + 2 * h + 1]);
      v[h][2 * jj] = bf_lo(r[t][m]); v[h][2 * jj + 1] = bf_hi(r[t][m]);
    }
    stsm4(rowa + t * 32, r[t][0], r[t][1], r[t][2], r[t][3]);
  }
}

__device__ __forceinline__ void combine_stats(const float2 (&pt)[8], float n, float& mean, float& rstd) {
  float m = 0.f;
#pragma unroll
  for (int i = 0; i < 8; i++) m += pt[i].x;
  m *= 0.125f;
  float m2 = 0.f;
#pragma unroll
  for (int i = 0; i < 8; i++) { const float d = pt[i].x - m; m2 += fmaf(n * d, d, pt[i].y); }
  mean = m;
  rstd = rsqrtf(m2 / (8.f * n) + 1e-5f);
}

__device__ __forceinline__ float gelu_tanh(float y) {
  const float u = y * fmaf(y * y, 0.044715f * 0.7978845608028654f, 0.7978845608028654f);
  const float hy = 0.5f * y;
  return fmaf(hy, tanh_fast(u), hy);
}

__device__ __forceinline__ void cluster_exit() {
  asm volatile("barrier.cluster.arrive.relaxed.aligned;\nbarrier.cluster.wait.aligned;" ::: "memory");
}

__global__ void __cluster_dims__(2, 1, 1) __launch_bounds__(NTHREADS, 1) fused_kernel(const __grid_constant__ Params p) {
  extern __shared__ __align__(1024) uint8_t smem_raw[];
  const uint32_t sb = smem_u32(smem_raw);
  const uint32_t bars = sb + SM_BARS;
  const int tid = threadIdx.x, warp = __shfl_sync(0xffffffffu, tid >> 5, 0), lane = tid & 31;
  const int b = blockIdx.x;
  const uint32_t rank = b & 1;
  const int cl = b >> 1, pp = cl & 3;
  const int r = 2 * (((cl >> 3) + pp) & 7) + ((cl >> 2) & 1), j = 2 * pp + rank;
  const int row0 = r * 128;
  trap_if((sb & 1023) != 0);
  TS(0);

  if (warp == 8) {
    if (elect_one()) {
      sts32(sb + SM_ZMASK, 0); sts32(sb + SM_ZMASK + 4, 0);
#pragma unroll 1
      for (int s = 0; s < 7; s++) { mbar_init(bars + B_FULL + 8 * s, 1); mbar_init(bars + B_EMPTY + 8 * s, USE_MC ? 4 : 2); }
      mbar_init(bars + B_MMADONE, USE_MC ? 4 : 2);
      mbar_init(bars + B_BFULL, 1); mbar_init(bars + B_BFULL1, 1); mbar_init(bars + B_XT, 1); mbar_init(bars + B_RAW0, 1); mbar_init(bars + B_XSFULL, 2);
      mbar_init(bars + B_STGFREE, 1); mbar_init(bars + B_RAW1, 1); mbar_init(bars + B_STGO, 8); mbar_init(bars + B_STGO + 8, 8);
      mbar_init(bars + B_P0A, 1); mbar_init(bars + B_P0B, USE_MC ? 2 : 1); mbar_init(bars + B_PHI, 1);
      asm volatile("fence.mbarrier_init.release.cluster;" ::: "memory");
      fence_async_smem();
      if (b < 80) {
        const int g = b / 10, kb = b % 10;
        mbar_expect_tx(bars + B_PHI, 3200);
        bulk_ld(sb + P0_PHIR, p.wphi + g * 1600, 3200, bars + B_PHI);
        mbar_expect_tx(bars + B_RAW0, 30720);
#pragma unroll
        for (int i = 0; i < 3; i++) tma_ld(sb + P0_RAW0 + i * 10240, &p.tmWq, 640 * i + 80 * g, 64 * kb, bars + B_RAW0);
      } else {
        const int i0 = b - 80, j0 = i0 / 10, k0 = i0 % 10;
        mbar_expect_tx(bars + B_RAW0, 24576);
        tma_ld(sb + P0_RAW0, &p.tmWi, 768 + 96 * j0, 64 * k0, bars + B_RAW0);
        tma_ld(sb + P0_RAW0 + 12288, &p.tmWi, 96 * j0, 64 * k0, bars + B_RAW0);
      }
    }
    __syncwarp();
  }
  if (tid == 0) {
    uint32_t old;
    asm volatile("atom.relaxed.gpu.global.add.u32 %0, [%1], 1;" : "=r"(old) : "l"(g_flags + F_CNT * 32) : "memory");
    sts32(sb + SM_ZMASK + 8, (old >> 7) + 1);
  }
  __syncthreads();
  asm volatile("barrier.cluster.arrive.relaxed.aligned;" ::: "memory");
  const uint32_t e1 = lds32(sb + SM_ZMASK + 8);
  prologue_stage0(p, sb, b, j, row0, tid, warp, lane);
  asm volatile("barrier.cluster.wait.aligned;" ::: "memory");
  const uint32_t peer_bars = mapa(bars, rank ^ 1);
  TS(1);

  if (warp >= 8) {
    asm volatile("setmaxnreg.dec.sync.aligned.u32 88;");
    if (warp == 8) {
      if (elect_one()) {
        uint32_t ph = 0, pmma = 0, pstg = 0;
        auto acquire = [&](int s) { mbar_wait(bars + B_EMPTY + 8 * s, ((ph >> s) & 1) ^ 1); ph ^= 1u << s; };
#pragma unroll 1
        for (int layer = 0; layer < 2; layer++) {
          const uint8_t* wb = g_wqkv + (size_t)j * 10 * 30720;
          const CUtensorMap* tmx = layer == 0 ? &p.tmAx64 : &p.tmX64;
          const int xrow = row0 + (layer == 0 ? 0 : S_);
          int s;
          if (layer == 0) {
#pragma unroll 1
            for (s = 0; s < 3; s++) {
              acquire(s);
              mbar_expect_tx(bars + B_FULL + 8 * s, 16384 + 30720);
              load_a(sb + s * 47104, tmx, s * 64, xrow, rank, bars + B_FULL + 8 * s);
            }
            mbar_wait(bars + B_P0A, 0);
            wait_flag(g_flags + (F_WQ + j) * 32, e1 * 10);
            TSP(2);
#pragma unroll 1
            for (s = 0; s < 3; s++) bulk_ld(sb + s * 47104 + 16384, wb + (size_t)s * 30720, 30720, bars + B_FULL + 8 * s);
            mbar_wait(bars + B_P0B, 0);
            acquire(3);
            mbar_expect_tx(bars + B_FULL + 24, 16384 + 30720);
            load_a(sb + 3 * 47104, tmx, 3 * 64, xrow, rank, bars + B_FULL + 24);
            bulk_ld(sb + 3 * 47104 + 16384, wb + (size_t)3 * 30720, 30720, bars + B_FULL + 24);
          } else {
#pragma unroll 1
            for (s = 0; s < 4; s++) {
              acquire(s);
              mbar_expect_tx(bars + B_FULL + 8 * s, 16384 + 30720);
              if (s < 2) bulk_ld(sb + s * 47104 + 16384, wb + (size_t)s * 30720, 30720, bars + B_FULL + 8 * s);
            }
            wait_flag(g_flags + (F_X2 + r) * 32, e1 * 8);
            TSP(69 + layer * 24);
#pragma unroll
            for (s = 0; s < 4; s++) {
              load_a(sb + s * 47104, tmx, s * 64, xrow, rank, bars + B_FULL + 8 * s);
              if (s >= 2) bulk_ld(sb + s * 47104 + 16384, wb + (size_t)s * 30720, 30720, bars + B_FULL + 8 * s);
            }
          }
          s = 0;
#pragma unroll 1
          for (int kb = 4; kb < 10; kb++) {
            acquire(s);
            mbar_expect_tx(bars + B_FULL + 8 * s, 16384 + 30720);
            load_a(sb + s * 47104, tmx, kb * 64, xrow, rank, bars + B_FULL + 8 * s);
            bulk_ld(sb + s * 47104 + 16384, wb + (size_t)kb * 30720, 30720, bars + B_FULL + 8 * s);
            s = (s + 1) & 3;
          }
          mbar_wait(bars + B_MMADONE, pmma); pmma ^= 1;
          if (layer == 0) wait_flag(g_flags + F_WREST * 32, e1 * 128);
          mbar_expect_tx(bars + B_BFULL, 40960);
          bulk_ld(sb + SM_WO, g_wo + (size_t)j * 102400, 40960, bars + B_BFULL);
          mbar_expect_tx(bars + B_BFULL1, 61440);
          bulk_ld(sb + SM_WO + 40960, g_wo + (size_t)j * 102400 + 40960, 30720, bars + B_BFULL1);
          bulk_ld(sb + SM_WO + 71680, g_wo + (size_t)j * 102400 + 71680, 30720, bars + B_BFULL1);
#pragma unroll 1
          for (s = 0; s < 3; s++) { acquire(s); mbar_expect_tx(bars + B_FULL + 8 * s, 32768); }
          wait_flag(g_flags + (F_O + layer * 16 + r) * 32, e1 * 8);
          TSP(70 + layer * 24);
#pragma unroll
          for (int kb = 0; kb < 6; kb++) load_a(sb + kb * 16384, &p.tmO64, kb * 64, row0, rank, bars + B_FULL + 8 * (kb >> 1));
#pragma unroll 1
          for (s = 0; s < 2; s++) {
            acquire(s);
            mbar_expect_tx(bars + B_FULL + 8 * s, 32768);
            load_a(sb + s * 32768, &p.tmO64, (2 * s + 6) * 64, row0, rank, bars + B_FULL + 8 * s);
            load_a(sb + s * 32768 + 16384, &p.tmO64, (2 * s + 7) * 64, row0, rank, bars + B_FULL + 8 * s);
          }
          mbar_wait(bars + B_MMADONE, pmma); pmma ^= 1;
          const uint8_t* wi = g_win + (size_t)j * 10 * 24576;
#pragma unroll 1
          for (s = 0; s < 5; s++) {
            acquire(s);
            mbar_expect_tx(bars + B_FULL + 8 * s, 16384 + 24576);
            if (s < 2) bulk_ld(sb + s * 40960 + 16384, wi + (size_t)s * 24576, 24576, bars + B_FULL + 8 * s);
          }
          wait_flag(g_flags + (F_X1 + layer * 16 + r) * 32, e1 * 8);
          TSP(71 + layer * 24);
          const int x1row = row0 + (layer == 0 ? 0 : 2 * S_);
#pragma unroll
          for (s = 0; s < 5; s++) {
            load_a(sb + s * 40960, &p.tmX64, s * 64, x1row, rank, bars + B_FULL + 8 * s);
            if (s >= 2) bulk_ld(sb + s * 40960 + 16384, wi + (size_t)s * 24576, 24576, bars + B_FULL + 8 * s);
          }
#pragma unroll 1
          for (s = 0; s < 5; s++) {
            acquire(s);
            mbar_expect_tx(bars + B_FULL + 8 * s, 16384 + 24576);
            load_a(sb + s * 40960, &p.tmX64, (s + 5) * 64, x1row, rank, bars + B_FULL + 8 * s);
            bulk_ld(sb + s * 40960 + 16384, wi + (size_t)(s + 5) * 24576, 24576, bars + B_FULL + 8 * s);
          }
          mbar_wait(bars + B_MMADONE, pmma); pmma ^= 1;
#pragma unroll 1
          for (s = 0; s < 7; s++) {
            acquire(s);
            mbar_expect_tx(bars + B_FULL + 8 * s, 16384 + 12288);
            load_a(sb + s * 28672, &p.tmWsp, s * 64, row0, rank, bars + B_FULL + 8 * s);
          }
          {
            const uint32_t zmask = sb + SM_ZMASK + layer * 4;
            uint32_t ready = 0;
            s = 0;
#pragma unroll 1
            for (int kb = 0; kb < 32; kb++) {
              if (kb >= 7) {
                acquire(s);
                mbar_expect_tx(bars + B_FULL + 8 * s, 16384 + 12288);
                load_a(sb + s * 28672, &p.tmWsp, kb * 64, row0, rank, bars + B_FULL + 8 * s);
              }
              if (!((ready >> kb) & 1)) { ready = wait_smem_bit(zmask, kb); fence_async_global(); }
              if (kb == 0) TSP(72 + layer * 24);
              if (kb == 5) { mbar_wait(bars + B_STGFREE, pstg); pstg ^= 1; }
              tma_ld(sb + s * 28672 + 16384, &p.tmZ, kb * 64, 96 * j, bars + B_FULL + 8 * s);
              s = (s + 1 == 7) ? 0 : s + 1;
            }
          }
          mbar_wait(bars + B_MMADONE, pmma); pmma ^= 1;
          mbar_expect_tx(bars + B_BFULL, 40960);
          bulk_ld(sb + SM_WO, g_wout + (size_t)j * 122880, 40960, bars + B_BFULL);
#pragma unroll 1
          for (s = 0; s < 3; s++) { acquire(s); mbar_expect_tx(bars + B_FULL + 8 * s, 32768); }
          wait_flag(g_flags + (F_U + layer * 16 + r) * 32, e1 * 8);
          TSP(73 + layer * 24);
#pragma unroll
          for (int kb = 0; kb < 4; kb++) load_a(sb + kb * 16384, &p.tmU64, kb * 64, row0, rank, bars + B_FULL + 8 * (kb >> 1));
          mbar_expect_tx(bars + B_BFULL1, 61440);
          bulk_ld(sb + SM_WO + 40960, g_wout + (size_t)j * 122880 + 40960, 30720, bars + B_BFULL1);
          load_a(sb + 4 * 16384, &p.tmU64, 4 * 64, row0, rank, bars + B_FULL + 16);
          load_a(sb + 5 * 16384, &p.tmU64, 5 * 64, row0, rank, bars + B_FULL + 16);
          bulk_ld(sb + SM_WO + 71680, g_wout + (size_t)j * 122880 + 71680, 30720, bars + B_BFULL1);
#pragma unroll 1
          for (s = 0; s < 3; s++) {
            acquire(s);
            mbar_expect_tx(bars + B_FULL + 8 * s, s == 2 ? 32768 + 20480 : 32768);
            load_a(sb + s * 32768, &p.tmU64, (2 * s + 6) * 64, row0, rank, bars + B_FULL + 8 * s);
            load_a(sb + s * 32768 + 16384, &p.tmU64, (2 * s + 7) * 64, row0, rank, bars + B_FULL + 8 * s);
            if (s == 2) bulk_ld(sb + SM_WO, g_wout + (size_t)j * 122880 + 102400, 20480, bars + B_FULL + 16);
          }
          mbar_wait(bars + B_MMADONE, pmma); pmma ^= 1;
        }
      }
      __syncwarp();
    } else if (warp == 9) {
      if (elect_one()) {
        uint32_t ng = 0;
        auto go = [&]() { mbar_wait(bars + B_STGO + 8 * (ng & 1), (ng >> 1) & 1); ng++; };
        auto done = [&](int flag) { bulk_commit(); bulk_wait_all(); signal_flag(g_flags + flag * 32); };
        if (b < 80) {
          const int g = b / 10, kb = b % 10;
          bulk_st(g_wqkv + (size_t)b * 30720, sb + P0_IMG0, 30720);
          bulk_st(g_csq + (kb * 8 + g) * 240, sb + P0_CS2, 960);
          bulk_st(g_kv + g * 3840 + kb * 384, sb + P0_ZERO, 1536);
          bulk_st(g_kv + (8 + g) * 3840 + kb * 384, sb + P0_ZERO, 1536);
          bulk_commit(); bulk_wait_read();
          mbar_arrive(bars + B_P0A);
          bulk_wait_all();
          signal_flag(g_flags + (F_WQ + g) * 32);
        } else {
          const int i0 = b - 80;
          bulk_st(g_win + (size_t)i0 * 24576, sb + P0_IMG0, 24576);
          bulk_st(g_csi + ((i0 % 10) * 8 + i0 / 10) * 192, sb + P0_CS2, 768);
          bulk_commit(); bulk_wait_read();
          mbar_arrive(bars + B_P0A);
        }
        TSP(113);
        go();
        if (b < 80) {
          bulk_st(g_wo + (size_t)b * 10240, sb + P0_IMG1, 10240);
          bulk_st(g_wout + (size_t)b * 10240, sb + P0_IMG1 + 10240, 10240);
        } else if (b < 112) {
          const int i1 = b - 80 + 48;
          bulk_st(g_win + (size_t)i1 * 24576, sb + P0_IMG1, 24576);
          bulk_st(g_csi + ((i1 % 10) * 8 + i1 / 10) * 192, sb + P0_CS3, 768);
        } else {
          bulk_st(g_wout + (size_t)(80 + b - 112) * 10240, sb + P0_IMG1, 10240);
        }
        bulk_commit(); bulk_wait_read();
        mbar_arrive(bars + B_P0B);
        if (USE_MC) mbar_arrive_remote(peer_bars + B_P0B);
        bulk_wait_all();
        signal_flag(g_flags + F_WREST * 32);
        TSP(115);
        {
          const uint8_t* w = reinterpret_cast<const uint8_t*>(p.wsp) + (size_t)b * 65536;
#pragma unroll
          for (int i = 0; i < 4; i++) prefetch_l2_bulk(w + i * 16384, 16384);
        }
#pragma unroll 1
        for (int layer = 0; layer < 2; layer++) {
          go(); bulk_red_f32(g_kv + (layer * 8 + j) * 3840, sb + SM_KVS, 15360); done(F_KV + layer * 8 + j); TSP(74 + layer * 24);
          go(); tma_st(&p.tmO80, sb + SM_OST, 80 * j, row0); done(F_O + layer * 16 + r); TSP(75 + layer * 24);
          go(); tma_st(&p.tmX80, sb + SM_XT, 80 * j, row0 + (layer == 0 ? 0 : 2 * S_)); done(F_X1 + layer * 16 + r); TSP(76 + layer * 24);
          go(); tma_st(&p.tmZ, sb + SM_ZT0, row0, 96 * j); tma_st(&p.tmZ, sb + SM_ZT1, row0 + 64, 96 * j);
          bulk_commit(); bulk_wait_all();
          signal_flag(g_flags + (F_ZN + layer * 8 + j) * 32 + r);
          mbar_arrive(bars + B_STGFREE); TSP(78 + layer * 24);
          go(); tma_st(&p.tmUs64, sb + SM_UST, 96 * j, row0); tma_st(&p.tmUs32, sb + SM_UST + 16384, 96 * j + 64, row0);
          done(F_U + layer * 16 + r); TSP(79 + layer * 24);
          go();
          if (layer == 0) {
            tma_st(&p.tmX80, sb + SM_XT, 80 * j, row0 + S_); done(F_X2 + r); TSP(80);
          } else {
            tma_st(&p.tmOut80, sb + SM_XT, 80 * j, row0);
            bulk_commit(); bulk_wait_all();
          }
        }
      }
      __syncwarp();
    } else {
      const int t = tid - 320;
#pragma unroll 1
      for (int it = 0; it < 4; it++) {
        if (it == 0) {
          if (t == 0) wait_flag(g_flags + (F_WQ + j) * 32, e1 * 10);
          bar_sync(4, 64);
#pragma unroll 1
          for (int n = t; n < 240; n += 64) {
            float s = 0.f;
#pragma unroll
            for (int kb = 0; kb < 10; kb++) s += ld_cg_f(g_csq + (kb * 8 + j) * 240 + n);
            const int jj = n >> 3, q = (n >> 1) & 3, e = 2 * jj + (n & 1);
            asm volatile("st.shared.f32 [%0], %1;" ::"r"(sb + SM_CSQ + (q * 60 + e) * 4), "f"(s) : "memory");
          }
#pragma unroll 1
          for (int n = t; n < 128; n += 64)
            asm volatile("st.shared.f32 [%0], %1;" ::"r"(sb + SM_BSP + n * 4), "f"(__bfloat162float(p.bsp[row0 + n])) : "memory");
        } else if (it == 1) {
          if (t == 0) wait_flag(g_flags + F_WREST * 32, e1 * 128);
          bar_sync(4, 64);
#pragma unroll 1
          for (int n = t; n < 192; n += 64) {
            float s = 0.f;
#pragma unroll
            for (int kb = 0; kb < 10; kb++) s += ld_cg_f(g_csi + (kb * 8 + j) * 192 + n);
            asm volatile("st.shared.f32 [%0], %1;" ::"r"(sb + SM_CSI + n * 4), "f"(s) : "memory");
          }
        }
#pragma unroll
        for (int h = 0; h < 2; h++) {
          const int row = t + 64 * h;
          float2 pt[8];
          uint32_t spins = 0;
          while (true) {
            bool ok = true;
#pragma unroll
            for (int i = 0; i < 8; i++) ok &= ld_tagged(g_xstat + (r * 8 + i) * 128 + row, e1 * 4 + it, pt[i]);
            if (ok) break;
            trap_if(++spins > SPIN_LIMIT);
            __nanosleep(200);
          }
          float mean, rstd;
          combine_stats(pt, 80.f, mean, rstd);
          sts64f(sb + SM_ROWSTAT + row * 8, mean, rstd);
        }
        __syncwarp();
        if (lane == 0) mbar_arrive(bars + B_XSFULL);
        if ((it & 1) && warp == 10) {
          const int layer = it >> 1;
          const uint32_t* zf = g_flags + (F_ZN + layer * 8 + j) * 32;
          uint32_t mask = 0, spins = 0;
          while (mask != 0xffffffffu) {
            const uint32_t m = __ballot_sync(0xffffffffu, (int32_t)(ld_acquire(zf + (lane >> 1)) - e1) >= 0);
            if (m != mask) { mask = m; if (lane == 0) sts32(sb + SM_ZMASK + layer * 4, mask); }
            trap_if(++spins > SPIN_LIMIT);
          }
        }
      }
    }
    cluster_exit();
  } else {
    asm volatile("setmaxnreg.inc.sync.aligned.u32 208;");
    const int wg = warp >> 2, w = warp & 3, q = lane & 3, rw = lane >> 2;
    const bool elect = (tid & 127) == 0;
    uint32_t ph = 0, pxs = 0, pbf = 0;
    const int R0 = 64 * wg + 16 * w + rw;
    uint32_t ng = 0;
    auto stage_done = [&]() { fence_async_smem(); __syncwarp(); if (lane == 0) mbar_arrive(bars + B_STGO + 8 * (ng & 1)); ng++; };
    uint4* const xstat = g_xstat + (r * 8 + j) * 128;
    prologue_stage1(sb, b, warp, lane, xstat, e1 * 4);
    ng = 1;
#pragma unroll 1
    for (int layer = 0; layer < 2; layer++) {
      {
        float acc[120];
        mainloop<240, 4, 47104, 1, false>(acc, 10, sb, 16384, wg, elect, ph, peer_bars, 64 + layer * 24);
        TS(4 + layer * 24);
        mbar_wait(bars + B_XSFULL, pxs); pxs ^= 1;
        const uint32_t csa = sb + SM_CSQ + q * 240;
        float sa[2], st[2], va[2], vt[2];
#pragma unroll
        for (int h = 0; h < 2; h++) {
          const float2 ms = lds64f(sb + SM_ROWSTAT + (R0 + 8 * h) * 8);
          va[h] = ms.y; vt[h] = -ms.x * ms.y;
          sa[h] = ms.y * 1.4426950408889634f; st[h] = vt[h] * 1.4426950408889634f;
        }
        const uint32_t rowoff0 = (R0 >> 3) * 128 + (R0 & 7) * 16;
        auto affine = [&](int base, uint32_t csoff, int h, float (&y)[20]) {
#pragma unroll
          for (int i = 0; i < 5; i++) {
            const float4 c = lds128f(csa + csoff + i * 16);
            y[4 * i + 0] = fmaf(c.x, st[h], acc[base + 8 * i + 2 * h] * sa[h]);
            y[4 * i + 1] = fmaf(c.y, st[h], acc[base + 8 * i + 2 * h + 1] * sa[h]);
            y[4 * i + 2] = fmaf(c.z, st[h], acc[base + 8 * i + 4 + 2 * h] * sa[h]);
            y[4 * i + 3] = fmaf(c.w, st[h], acc[base + 8 * i + 4 + 2 * h + 1] * sa[h]);
          }
        };
        bar_sync(1, 256);
        TS(19 + layer * 24);
#pragma unroll
        for (int h = 0; h < 2; h++) {
          uint32_t vv[10];
#pragma unroll
          for (int i = 0; i < 5; i++) {
            const float4 c = lds128f(csa + 160 + i * 16);
            vv[2 * i] = pack_bf16(fmaf(c.x, vt[h], acc[80 + 8 * i + 2 * h] * va[h]), fmaf(c.y, vt[h], acc[80 + 8 * i + 2 * h + 1] * va[h]));
            vv[2 * i + 1] = pack_bf16(fmaf(c.z, vt[h], acc[80 + 8 * i + 4 + 2 * h] * va[h]), fmaf(c.w, vt[h], acc[80 + 8 * i + 4 + 2 * h + 1] * va[h]));
          }
          const uint32_t vb = sb + SM_VST + q * VST_HEAD + rowoff0 + h * 128;
          sts128(vb, vv[0], vv[1], vv[2], vv[3]);
          sts128(vb + 2048, vv[4], vv[5], vv[6], vv[7]);
          sts128(vb + 4096, vv[8], vv[9], 0x00003f80u, 0u);
        }
#pragma unroll
        for (int h = 0; h < 2; h++) {
          float y[20];
          affine(40, 80, h, y);
          uint32_t o[20];
          feature_map(y, o);
#pragma unroll
          for (int c = 0; c < 5; c++) sts128(sb + SM_PHI + q * PHI_HEAD + c * 2048 + rowoff0 + h * 128, o[4 * c], o[4 * c + 1], o[4 * c + 2], o[4 * c + 3]);
        }
        TS(20 + layer * 24);
        fence_async_smem();
        bar_sync(1, 256);
        TS(21 + layer * 24);
        uint32_t qf[20];
        {
          float kva[20], kvb[20];
#pragma unroll
          for (int i = 0; i < 20; i++) { kva[i] = 0.f; kvb[i] = 0.f; }
          const uint32_t h0 = 2 * wg;
          const uint64_t dv = make_desc(sb + SM_VST + h0 * VST_HEAD, 128, 2048, 0), dp = make_desc(sb + SM_PHI + h0 * PHI_HEAD, 128, 2048, 0);
          fence_regs(kva); fence_regs(kvb);
          wgmma_fence();
#pragma unroll
          for (int ks = 0; ks < 8; ks++) {
            wgmma_ss_n40<1, 1>(kva, dv + ks * 16, dp + ks * 16, 1);
            wgmma_ss_n40<1, 1>(kvb, dv + (VST_HEAD >> 4) + ks * 16, dp + (PHI_HEAD >> 4) + ks * 16, 1);
          }
          wgmma_commit();
          {
            float y[20];
            affine(0, 0, 0, y);
            feature_map(y, qf);
          }
          wgmma_wait<0>();
          fence_regs(kva); fence_regs(kvb);
          TS(22 + layer * 24);
          if (w < 2) {
#pragma unroll
            for (int h = 0; h < 2; h++) {
              const int d = 16 * w + 8 * h + rw;
              if (d < 24) {
#pragma unroll
                for (int jj = 0; jj < 5; jj++) {
                  sts64f(sb + SM_KVS + ((h0 * 24 + d) * 40 + 8 * jj + 2 * q) * 4, kva[4 * jj + 2 * h], kva[4 * jj + 2 * h + 1]);
                  sts64f(sb + SM_KVS + (((h0 + 1) * 24 + d) * 40 + 8 * jj + 2 * q) * 4, kvb[4 * jj + 2 * h], kvb[4 * jj + 2 * h + 1]);
                }
              }
            }
          }
        }
        stage_done();
        bar_sync(1, 256);
        TS(5 + layer * 24);
        const uint32_t pq = sb + SM_PHI + q * PHI_HEAD + rowoff0;
#pragma unroll
        for (int c = 0; c < 5; c++) sts128(pq + c * 2048, qf[4 * c], qf[4 * c + 1], qf[4 * c + 2], qf[4 * c + 3]);
        sts128(pq + 5 * 2048, 0u, 0u, 0u, 0u);
        {
          float y[20];
          affine(0, 0, 1, y);
          feature_map(y, qf);
#pragma unroll
          for (int c = 0; c < 5; c++) sts128(pq + 128 + c * 2048, qf[4 * c], qf[4 * c + 1], qf[4 * c + 2], qf[4 * c + 3]);
          sts128(pq + 128 + 5 * 2048, 0u, 0u, 0u, 0u);
        }
      }
      TS(6 + layer * 24);
      if (tid == 0) wait_flag(g_flags + (F_KV + layer * 8 + j) * 32, e1 * 16);
      bar_sync(1, 256);
      TS(7 + layer * 24);
      {
        const float* kvg = g_kv + (layer * 8 + j) * 3840;
        float4 la[2], lc[2];
#pragma unroll
        for (int u = 0; u < 2; u++) {
          const int i = tid + 256 * u;
          if (i < 480) { la[u] = ld_cg_f4(kvg + i * 8); lc[u] = ld_cg_f4(kvg + i * 8 + 4); }
        }
        if (tid < 96) sts128(sb + SM_KVB + (tid / 24) * KVB_HEAD + ((tid % 24) >> 3) * 768 + 5 * 128 + (tid & 7) * 16, 0u, 0u, 0u, 0u);
#pragma unroll
        for (int u = 0; u < 2; u++) {
          const int i = tid + 256 * u;
          if (i < 480) {
            const int hd = i / 120, n = (i % 120) / 5, kg = i % 5;
            sts128(sb + SM_KVB + hd * KVB_HEAD + (n >> 3) * 768 + kg * 128 + (n & 7) * 16, pack_bf16(la[u].x, la[u].y), pack_bf16(la[u].z, la[u].w),
                   pack_bf16(lc[u].x, lc[u].y), pack_bf16(lc[u].z, lc[u].w));
          }
        }
        TS(23 + layer * 24);
        fence_async_smem();
        bar_sync(1, 256);
        TS(24 + layer * 24);
        float oa[4][12];
#pragma unroll
        for (int hd = 0; hd < 4; hd++)
#pragma unroll
          for (int i = 0; i < 12; i++) oa[hd][i] = 0.f;
#pragma unroll
        for (int hd = 0; hd < 4; hd++) fence_regs(oa[hd]);
        const uint64_t dq = make_desc(sb + SM_PHI + wg * 1024, 2048, 128, 0), dk = make_desc(sb + SM_KVB, 128, 768, 0);
        wgmma_fence();
#pragma unroll
        for (int hd = 0; hd < 4; hd++)
#pragma unroll
          for (int ks = 0; ks < 3; ks++)
            wgmma_ss_n24<0, 0>(oa[hd], dq + hd * (PHI_HEAD >> 4) + ks * 256, dk + hd * (KVB_HEAD >> 4) + ks * 16, 1);
        wgmma_commit();
        wgmma_wait<0>();
#pragma unroll
        for (int hd = 0; hd < 4; hd++) fence_regs(oa[hd]);
        TS(25 + layer * 24);
#pragma unroll
        for (int hd = 0; hd < 4; hd++)
#pragma unroll
          for (int h = 0; h < 2; h++) {
            const float inv = rcp(__shfl_sync(0xffffffffu, oa[hd][8 + 2 * h], (lane & ~3) | 2) + 1e-6f);
            const uint32_t ob = sb + SM_OST + (R0 + 8 * h) * 160 + hd * 40 + q * 4;
            sts32(ob, pack_bf16(oa[hd][2 * h] * inv, oa[hd][2 * h + 1] * inv));
            sts32(ob + 16, pack_bf16(oa[hd][4 + 2 * h] * inv, oa[hd][4 + 2 * h + 1] * inv));
            if (q < 2) sts32(ob + 32, pack_bf16(oa[hd][8 + 2 * h] * inv, oa[hd][8 + 2 * h + 1] * inv));
          }
        stage_done();
      }
      TS(8 + layer * 24);
      {
        float acc[40];
        mainloop<80, 3, 32768, 2, true>(acc, 5, sb, SM_WO, wg, elect, ph, peer_bars, 65 + layer * 24, pbf);
        pbf ^= 1;
        TS(9 + layer * 24);
        float v[2][20];
        residual_update(acc, v, sb, wg, w, lane);
        stage_done();
        TS(10 + layer * 24);
#pragma unroll
        for (int h = 0; h < 2; h++) {
          float mean, m2;
          row_partial_stats<20>(v[h], 1.f / 80.f, mean, m2);
          if (q == 0) st_tagged(xstat + R0 + 8 * h, mean, m2, e1 * 4 + 1 + 2 * layer);
        }
      }
      uint32_t z1p[24];
      {
        float acc[96];
        mainloop<192, 5, 40960, 1, false>(acc, 10, sb, 16384, wg, elect, ph, peer_bars, 66 + layer * 24);
        TS(11 + layer * 24);
        mbar_wait(bars + B_XSFULL, pxs); pxs ^= 1;
        float la[2], lt[2];
#pragma unroll
        for (int h = 0; h < 2; h++) {
          const float2 ms = lds64f(sb + SM_ROWSTAT + (R0 + 8 * h) * 8);
          la[h] = ms.y; lt[h] = -ms.x * ms.y;
        }
#pragma unroll
        for (int jj = 0; jj < 12; jj++) {
          const float2 c = lds64f(sb + SM_CSI + (8 * jj + 2 * q) * 4);
#pragma unroll
          for (int h = 0; h < 2; h++) {
            acc[4 * jj + 2 * h] = gelu_tanh(fmaf(c.x, lt[h], acc[4 * jj + 2 * h] * la[h]));
            acc[4 * jj + 2 * h + 1] = gelu_tanh(fmaf(c.y, lt[h], acc[4 * jj + 2 * h + 1] * la[h]));
          }
        }
#pragma unroll
        for (int h = 0; h < 2; h++) {
          float v[24];
#pragma unroll
          for (int jj = 0; jj < 12; jj++) { v[2 * jj] = acc[4 * jj + 2 * h]; v[2 * jj + 1] = acc[4 * jj + 2 * h + 1]; }
          float mean, m2;
          row_partial_stats<24>(v, 1.f / 96.f, mean, m2);
          if (q == 0) st_tagged(g_zstat + (r * 8 + j) * 128 + R0 + 8 * h, mean, m2, e1 * 2 + layer);
        }
        TS(12 + layer * 24);
#pragma unroll
        for (int jj = 0; jj < 12; jj++) {
          const float2 c = lds64f(sb + SM_CSI + (96 + 8 * jj + 2 * q) * 4);
#pragma unroll
          for (int h = 0; h < 2; h++)
            z1p[2 * jj + h] = pack_bf16(gelu_tanh(fmaf(c.x, lt[h], acc[48 + 4 * jj + 2 * h] * la[h])),
                                        gelu_tanh(fmaf(c.y, lt[h], acc[48 + 4 * jj + 2 * h + 1] * la[h])));
        }
        float2 p0[2], p1[2];
        {
          const uint4* zs = g_zstat + (r * 8 + 2 * q) * 128 + R0;
          uint32_t spins = 0;
          while (true) {
            bool ok = ld_tagged(zs, e1 * 2 + layer, p0[0]);
            ok &= ld_tagged(zs + 128, e1 * 2 + layer, p1[0]);
            ok &= ld_tagged(zs + 8, e1 * 2 + layer, p0[1]);
            ok &= ld_tagged(zs + 128 + 8, e1 * 2 + layer, p1[1]);
            if (__all_sync(0xffffffffu, ok)) break;
            trap_if(++spins > SPIN_LIMIT);
          }
        }
        bar_sync(1, 256);
        TS(13 + layer * 24);
        float zm[2], zr[2];
#pragma unroll
        for (int h = 0; h < 2; h++) {
          float m = p0[h].x + p1[h].x;
          m += __shfl_xor_sync(0xffffffffu, m, 1);
          m += __shfl_xor_sync(0xffffffffu, m, 2);
          m *= 0.125f;
          const float d0 = p0[h].x - m, d1 = p1[h].x - m;
          float m2 = p0[h].y + p1[h].y + 96.f * (d0 * d0 + d1 * d1);
          m2 += __shfl_xor_sync(0xffffffffu, m2, 1);
          m2 += __shfl_xor_sync(0xffffffffu, m2, 2);
          zr[h] = rsqrtf(m2 * (1.f / 768.f) + 1e-5f);
          zm[h] = -m * zr[h];
        }
        const uint32_t zb = sb + (wg == 0 ? SM_ZT0 : SM_ZT1);
#pragma unroll
        for (int t = 0; t < 6; t++) {
          uint32_t x[4];
#pragma unroll
          for (int m = 0; m < 4; m++) {
            const int h = m & 1, jj = 2 * t + (m >> 1);
            x[m] = pack_bf16(fmaf(acc[4 * jj + 2 * h], zr[h], zm[h]), fmaf(acc[4 * jj + 2 * h + 1], zr[h], zm[h]));
          }
          const int m = lane >> 3, i = lane & 7, f = 8 * (2 * t + (m >> 1)) + i, c = 2 * w + (m & 1);
          stsm4t(zb + f * 128 + ((c ^ i) << 4), x[0], x[1], x[2], x[3]);
        }
        stage_done();
      }
      TS(14 + layer * 24);
      {
        float acc[48];
        mainloop<96, 7, 28672, 1, false>(acc, 32, sb, 16384, wg, elect, ph, peer_bars, 67 + layer * 24);
        TS(15 + layer * 24);
        bar_sync(1, 256);
        const float b0 = lds32f(sb + SM_BSP + R0 * 4), b1 = lds32f(sb + SM_BSP + (R0 + 8) * 4);
        const int m = lane >> 3, row = 64 * wg + 16 * w + 8 * (m & 1) + (lane & 7);
#pragma unroll
        for (int t = 0; t < 6; t++) {
          uint32_t x[4];
#pragma unroll
          for (int mm = 0; mm < 4; mm++) {
            const int h = mm & 1, jj = 2 * t + (mm >> 1);
            const float bb = h ? b1 : b0;
            const uint32_t z = z1p[2 * jj + h];
            x[mm] = pack_bf16(bf_lo(z) * (acc[4 * jj + 2 * h] + bb), bf_hi(z) * (acc[4 * jj + 2 * h + 1] + bb));
          }
          const int jj = 2 * t + (m >> 1);
          const uint32_t a = t < 4 ? sb + SM_UST + row * 128 + ((jj ^ (row & 7)) << 4)
                                   : sb + SM_UST + 16384 + row * 64 + (((jj - 8) ^ ((row >> 1) & 3)) << 4);
          stsm4(a, x[0], x[1], x[2], x[3]);
        }
        stage_done();
      }
      TS(16 + layer * 24);
      {
        float acc[40];
        mainloop<80, 3, 32768, 2, true>(acc, 6, sb, SM_WO, wg, elect, ph, peer_bars, 68 + layer * 24, pbf);
        pbf ^= 1;
        TS(17 + layer * 24);
        float v[2][20];
        residual_update(acc, v, sb, wg, w, lane);
        stage_done();
        TS(18 + layer * 24);
        if (layer == 0) {
#pragma unroll
          for (int h = 0; h < 2; h++) {
            float mean, m2;
            row_partial_stats<20>(v[h], 1.f / 80.f, mean, m2);
            if (q == 0) st_tagged(xstat + R0 + 8 * h, mean, m2, e1 * 4 + 2);
          }
        }
      }
    }
    cluster_exit();
  }
}

typedef CUresult (*EncodeFn)(CUtensorMap*, CUtensorMapDataType, cuuint32_t, void*, const cuuint64_t*, const cuuint64_t*, const cuuint32_t*,
                             const cuuint32_t*, CUtensorMapInterleave, CUtensorMapSwizzle, CUtensorMapL2promotion, CUtensorMapFloatOOBfill);

void make_map(EncodeFn enc, CUtensorMap* tm, const void* ptr, uint64_t rows, uint64_t cols, uint32_t box_rows, uint32_t box_cols, CUtensorMapSwizzle sw) {
  cuuint64_t dims[2] = {cols, rows};
  cuuint64_t strides[1] = {cols * 2};
  cuuint32_t box[2] = {box_cols, box_rows};
  cuuint32_t es[2] = {1, 1};
  enc(tm, CU_TENSOR_MAP_DATA_TYPE_BFLOAT16, 2, const_cast<void*>(ptr), dims, strides, box, es, CU_TENSOR_MAP_INTERLEAVE_NONE, sw,
      CU_TENSOR_MAP_L2_PROMOTION_L2_256B, CU_TENSOR_MAP_FLOAT_OOB_FILL_NONE);
}

}

extern "C" void kernel_launch(void* const* d_in, const int* in_sizes, int n_in, void* d_out, int out_size) {
  (void)in_sizes; (void)n_in; (void)out_size;
  static EncodeFn enc = nullptr;
  static void *px = nullptr, *po = nullptr, *pu = nullptr, *pz = nullptr;
  if (!enc) {
    void* fn = nullptr;
    cudaDriverEntryPointQueryResult st;
    cudaGetDriverEntryPoint("cuTensorMapEncodeTiled", &fn, cudaEnableDefault, &st);
    enc = (EncodeFn)fn;
    cudaGetSymbolAddress(&px, g_x); cudaGetSymbolAddress(&po, g_o); cudaGetSymbolAddress(&pu, g_u); cudaGetSymbolAddress(&pz, g_zt);
    cudaFuncSetAttribute(fused_kernel, cudaFuncAttributeMaxDynamicSharedMemorySize, SMEM_BYTES);
  }
  Params p;
  const void* ax = d_in[0];
  const CUtensorMapSwizzle S128 = CU_TENSOR_MAP_SWIZZLE_128B, S64 = CU_TENSOR_MAP_SWIZZLE_64B, S0 = CU_TENSOR_MAP_SWIZZLE_NONE;
  make_map(enc, &p.tmAx64, ax, S_, D_, 64, 64, S128);
  make_map(enc, &p.tmAx80, ax, S_, D_, 128, 80, S0);
  make_map(enc, &p.tmX64, px, 3 * S_, D_, 64, 64, S128);
  make_map(enc, &p.tmX80, px, 3 * S_, D_, 128, 80, S0);
  make_map(enc, &p.tmOut80, d_out, S_, D_, 128, 80, S0);
  make_map(enc, &p.tmO64, po, S_, D_, 64, 64, S128);
  make_map(enc, &p.tmO80, po, S_, D_, 128, 80, S0);
  make_map(enc, &p.tmU64, pu, S_, FH_, 64, 64, S128);
  make_map(enc, &p.tmUs64, pu, S_, FH_, 128, 64, S128);
  make_map(enc, &p.tmUs32, pu, S_, FH_, 128, 32, S64);
  make_map(enc, &p.tmZ, pz, FH_, S_, 96, 64, S128);
  make_map(enc, &p.tmWsp, d_in[6], S_, S_, 64, 64, S128);
  make_map(enc, &p.tmWq, d_in[1], D_, 3 * D_, 64, 80, S0);
  make_map(enc, &p.tmWo, d_in[3], D_, D_, 64, 80, S0);
  make_map(enc, &p.tmWi, d_in[5], D_, 2 * FH_, 64, 96, S0);
  make_map(enc, &p.tmWout, d_in[8], FH_, D_, 64, 80, S0);
  p.wphi = (const __nv_bfloat16*)d_in[2];
  p.wsp = (const __nv_bfloat16*)d_in[6];
  p.bsp = (const __nv_bfloat16*)d_in[7];
  fused_kernel<<<NCTA, NTHREADS, SMEM_BYTES, cudaStreamPerThread>>>(p);
}
```

```cpp
#include <cuda_runtime.h>
#include <cuda_bf16.h>
#include <cuda.h>
#include <stdint.h>

#define P0_EARLY_NC 1

#define SLEEPNS 0

#define P5_DELAY 0

namespace {

constexpr int S_ = 2048, D_ = 640, FH_ = 768;
constexpr int NCTA = 128, NTHREADS = 384;

__device__ __align__(1024) uint8_t g_wqkv[8 * 10 * 30720];
__device__ __align__(1024) uint8_t g_win[8 * 10 * 24576];
__device__ __align__(1024) uint8_t g_wo[8 * 10 * 10240];
__device__ __align__(1024) uint8_t g_wout[8 * 12 * 10240];
__device__ __align__(128) float g_csq[10 * 8 * 240];
__device__ __align__(128) float g_csi[10 * 8 * 192];
__device__ __align__(128) __nv_bfloat16 g_x[3 * S_ * D_];
__device__ __align__(128) __nv_bfloat16 g_o[S_ * D_];
__device__ __align__(128) __nv_bfloat16 g_u[S_ * FH_];
__device__ __align__(128) __nv_bfloat16 g_zt[FH_ * S_];
__device__ __align__(128) float g_kv[2 * 8 * 3840];
__device__ __align__(128) uint4 g_xstat[16 * 8 * 128];
__device__ __align__(128) uint4 g_zstat[16 * 8 * 128];
__device__ __align__(128) uint32_t g_flags[256 * 32];

constexpr int F_CNT = 0, F_KV = 1, F_O = 17, F_X1 = 49, F_U = 113, F_X2 = 145, F_ZN = 161,
              F_WQ = 177, F_WREST = 185;

constexpr uint32_t SM_XT = 200 * 1024;
constexpr uint32_t SM_SMALL = SM_XT + 20480;
constexpr uint32_t SM_BARS = SM_SMALL;
constexpr uint32_t SM_CSQ = SM_SMALL + 256;
constexpr uint32_t SM_CSI = SM_SMALL + 1280;
constexpr uint32_t SM_ROWSTAT = SM_SMALL + 2048;
constexpr uint32_t SM_BSP = SM_SMALL + 4096;
constexpr uint32_t SM_ZMASK = SM_SMALL + 4608;
constexpr uint32_t SMEM_BYTES = 232448;

constexpr uint32_t B_FULL = 0, B_EMPTY = 64, B_MMADONE = 128, B_BFULL = 136, B_XT = 144, B_RAW0 = 152, B_XSFULL = 160,
                   B_STGFREE = 168, B_RAW1 = 176, B_STGO = 184  , B_P0A = 200, B_P0B = 208, B_PHI = 216, B_BFULL1 = 224, B_XSLOC = 232, B_ZNLOC = 240;

constexpr uint32_t SM_PHI = 0, PHI_HEAD = 12320;
constexpr uint32_t SM_VST = 49408, VST_HEAD = 6176;
constexpr uint32_t SM_KVS = 74240;
constexpr uint32_t SM_KVB = 89600, KVB_HEAD = 2304;
constexpr uint32_t SM_OST = 49408;
constexpr uint32_t SM_WO = 100 * 1024;
constexpr uint32_t SM_ZT0 = 5 * 28672 + 16384, SM_ZT1 = 6 * 28672 + 16384;
constexpr uint32_t SM_UST = 0;

struct Params {
  CUtensorMap tmAx64, tmAx80, tmX64, tmX80, tmOut80, tmO64, tmO80, tmU64, tmUs32, tmZ, tmWsp, tmWo, tmWi, tmWout;
  const __nv_bfloat16 *wqkv, *wphi, *wsp, *bsp;
};

__device__ __forceinline__ uint32_t smem_u32(const void* p) { return (uint32_t)__cvta_generic_to_shared(p); }
__device__ __forceinline__ void mbar_init(uint32_t bar, uint32_t cnt) { asm volatile("mbarrier.init.shared::cta.b64 [%0], %1;" ::"r"(bar), "r"(cnt)); }
__device__ __forceinline__ void mbar_expect_tx(uint32_t bar, uint32_t bytes) { asm volatile("mbarrier.arrive.expect_tx.shared::cta.b64 _, [%0], %1;" ::"r"(bar), "r"(bytes) : "memory"); }
__device__ __forceinline__ void mbar_arrive(uint32_t bar) { asm volatile("mbarrier.arrive.shared::cta.b64 _, [%0];" ::"r"(bar) : "memory"); }
constexpr uint32_t SPIN_LIMIT = 1u << 22;
__device__ __forceinline__ void mbar_wait(uint32_t bar, uint32_t parity) {
  asm volatile(
      "{\n.reg .pred p, t;\n.reg .u32 c;\nmov.u32 c, 0;\n"
      "MW_%=:\nmbarrier.try_wait.parity.shared::cta.b64 p, [%0], %1;\n@p bra MD_%=;\n"
      "add.u32 c, c, 1;\nsetp.gt.u32 t, c, %2;\n@t trap;\nbra MW_%=;\nMD_%=:\n}"
      ::"r"(bar), "r"(parity), "n"(SPIN_LIMIT) : "memory");
}
template <int NS> __device__ __forceinline__ void mbar_wait_long(uint32_t bar, uint32_t parity) {
  asm volatile(
      "{\n.reg .pred p, t;\n.reg .u32 c;\nmov.u32 c, 0;\n"
      "LW_%=:\nmbarrier.test_wait.parity.shared::cta.b64 p, [%0], %1;\n@p bra LD_%=;\n"
      "nanosleep.u32 %3;\nadd.u32 c, c, 1;\nsetp.gt.u32 t, c, %2;\n@t trap;\nbra LW_%=;\nLD_%=:\n}"
      ::"r"(bar), "r"(parity), "n"(SPIN_LIMIT), "n"(NS) : "memory");
}
__device__ __forceinline__ uint32_t ld_acquire(const uint32_t* p) { uint32_t v; asm volatile("ld.acquire.gpu.global.u32 %0, [%1];" : "=r"(v) : "l"(p) : "memory"); return v; }
__device__ __forceinline__ void signal_flag(uint32_t* p) {
  asm volatile("fence.proxy.async.global;\nred.release.gpu.global.add.u32 [%0], 1;" ::"l"(p) : "memory");
}
__device__ __forceinline__ void wait_flag(const uint32_t* p, uint32_t target) {
  asm volatile(
      "{\n.reg .pred p, t;\n.reg .u32 c, v;\nmov.u32 c, 0;\n"
      "FW_%=:\nld.acquire.gpu.global.u32 v, [%0];\nsub.u32 v, v, %1;\nsetp.ge.s32 p, v, 0;\n@p bra FD_%=;\n"
      "add.u32 c, c, 1;\nsetp.gt.u32 t, c, %2;\n@t trap;\nbra FW_%=;\nFD_%=:\nfence.proxy.async.global;\n}"
      ::"l"(p), "r"(target), "n"(SPIN_LIMIT) : "memory");
}
__device__ __forceinline__ uint32_t wait_smem_bit(uint32_t addr, uint32_t bit) {
  uint32_t v;
  asm volatile(
      "{\n.reg .pred p, t;\n.reg .u32 c, m;\nmov.u32 c, 0;\n"
      "BW_%=:\nld.volatile.shared.u32 %0, [%1];\nshr.u32 m, %0, %2;\nand.b32 m, m, 1;\nsetp.ne.u32 p, m, 0;\n@p bra BD_%=;\n"
      "add.u32 c, c, 1;\nsetp.gt.u32 t, c, %3;\n@t trap;\nbra BW_%=;\nBD_%=:\n}"
      : "=r"(v) : "r"(addr), "r"(bit), "n"(SPIN_LIMIT * 8) : "memory");
  return v;
}
__device__ __forceinline__ bool elect_one() {
  uint32_t p;
  asm volatile("{\n.reg .pred P;\nelect.sync _|P, 0xffffffff;\nselp.u32 %0, 1, 0, P;\n}" : "=r"(p));
  return p;
}
__device__ __forceinline__ void trap_if(bool c) { asm volatile("{\n.reg .pred t;\nsetp.ne.u32 t, %0, 0;\n@t trap;\n}" ::"r"((uint32_t)c)); }
__device__ __forceinline__ void st_tagged(uint4* p, float a, float b, uint32_t tag) {
  const uint64_t w0 = ((uint64_t)tag << 32) | __float_as_uint(a), w1 = ((uint64_t)tag << 32) | __float_as_uint(b);
  asm volatile("st.relaxed.gpu.global.v2.b64 [%0], {%1, %2};" ::"l"(p), "l"(w0), "l"(w1) : "memory");
}
template <int OFF = 0> __device__ __forceinline__ bool ld_tagged(const uint4* p, uint32_t tag, float2& v) {
  uint64_t w0, w1;
  asm volatile("ld.relaxed.gpu.global.v2.b64 {%0, %1}, [%2 + %3];" : "=l"(w0), "=l"(w1) : "l"(p), "n"(OFF * 16) : "memory");
  v.x = __uint_as_float((uint32_t)w0); v.y = __uint_as_float((uint32_t)w1);
  return (uint32_t)(w0 >> 32) == tag && (uint32_t)(w1 >> 32) == tag;
}
__device__ __forceinline__ float ld_cg_f(const float* p) { float v; asm volatile("ld.relaxed.gpu.global.f32 %0, [%1];" : "=f"(v) : "l"(p) : "memory"); return v; }
__device__ __forceinline__ float4 ld_cg_f4(const float* p) {
  float4 v; asm volatile("ld.global.cg.v4.f32 {%0, %1, %2, %3}, [%4];" : "=f"(v.x), "=f"(v.y), "=f"(v.z), "=f"(v.w) : "l"(p) : "memory"); return v;
}
__device__ __forceinline__ void tma_ld(uint32_t dst, const CUtensorMap* tm, int c0, int c1, uint32_t bar) {
  asm volatile("cp.async.bulk.tensor.2d.shared::cluster.global.mbarrier::complete_tx::bytes [%0], [%1, {%3, %4}], [%2];"
               ::"r"(dst), "l"(tm), "r"(bar), "r"(c0), "r"(c1) : "memory");
}
__device__ __forceinline__ void tma_st(const CUtensorMap* tm, uint32_t src, int c0, int c1) {
  asm volatile("cp.async.bulk.tensor.2d.global.shared::cta.bulk_group [%0, {%2, %3}], [%1];" ::"l"(tm), "r"(src), "r"(c0), "r"(c1) : "memory");
}
__device__ __forceinline__ void bulk_ld(uint32_t dst, const void* src, uint32_t bytes, uint32_t bar) {
  asm volatile("cp.async.bulk.shared::cluster.global.mbarrier::complete_tx::bytes [%0], [%1], %2, [%3];" ::"r"(dst), "l"(src), "r"(bytes), "r"(bar) : "memory");
}
__device__ __forceinline__ void bulk_st(void* dst, uint32_t src, uint32_t bytes) {
  asm volatile("cp.async.bulk.global.shared::cta.bulk_group [%0], [%1], %2;" ::"l"(dst), "r"(src), "r"(bytes) : "memory");
}
__device__ __forceinline__ void bulk_red_f32(void* dst, uint32_t src, uint32_t bytes) {
  asm volatile("cp.reduce.async.bulk.global.shared::cta.bulk_group.add.f32 [%0], [%1], %2;" ::"l"(dst), "r"(src), "r"(bytes) : "memory");
}
__device__ __forceinline__ void bulk_commit() { asm volatile("cp.async.bulk.commit_group;" ::: "memory"); }
__device__ __forceinline__ void bulk_wait_all() { asm volatile("cp.async.bulk.wait_group 0;" ::: "memory"); }
__device__ __forceinline__ void bulk_wait_read() { asm volatile("cp.async.bulk.wait_group.read 0;" ::: "memory"); }
__device__ __forceinline__ void fence_async_global() { asm volatile("fence.proxy.async.global;" ::: "memory"); }
__device__ __forceinline__ void fence_async_smem() { asm volatile("fence.proxy.async.shared::cta;" ::: "memory"); }
__device__ __forceinline__ void bar_sync(int id, int n) { asm volatile("bar.sync %0, %1;" ::"r"(id), "r"(n) : "memory"); }
__device__ __forceinline__ void wgmma_fence() { asm volatile("wgmma.fence.sync.aligned;" ::: "memory"); }
__device__ __forceinline__ void wgmma_commit() { asm volatile("wgmma.commit_group.sync.aligned;" ::: "memory"); }
template <int N> __device__ __forceinline__ void wgmma_wait() { asm volatile("wgmma.wait_group.sync.aligned %0;" ::"n"(N) : "memory"); }
__device__ __forceinline__ uint64_t make_desc(uint32_t addr, uint32_t lbo, uint32_t sbo, uint32_t mode) {
  return (uint64_t)((addr & 0x3FFFF) >> 4) | ((uint64_t)(lbo >> 4) << 16) | ((uint64_t)(sbo >> 4) << 32) | ((uint64_t)mode << 62);
}
__device__ __forceinline__ uint64_t desc_k128(uint32_t addr) { return make_desc(addr, 16, 1024, 1); }
__device__ __forceinline__ uint32_t pack_bf16(float lo, float hi) { uint32_t r; asm("cvt.rn.bf16x2.f32 %0, %1, %2;" : "=r"(r) : "f"(hi), "f"(lo)); return r; }
__device__ __forceinline__ float bf_lo(uint32_t v) { return __uint_as_float(v << 16); }
__device__ __forceinline__ float bf_hi(uint32_t v) { return __uint_as_float(v & 0xffff0000u); }
__device__ __forceinline__ float ex2(float x) { float y; asm("ex2.approx.ftz.f32 %0, %1;" : "=f"(y) : "f"(x)); return y; }
__device__ __forceinline__ float rcp(float x) { float y; asm("rcp.approx.ftz.f32 %0, %1;" : "=f"(y) : "f"(x)); return y; }
__device__ __forceinline__ float tanh_fast(float x) { float y; asm("tanh.approx.f32 %0, %1;" : "=f"(y) : "f"(x)); return y; }
__device__ __forceinline__ void sts32(uint32_t a, uint32_t v) { asm volatile("st.shared.u32 [%0], %1;" ::"r"(a), "r"(v) : "memory"); }
__device__ __forceinline__ void sts64f(uint32_t a, float x, float y) { asm volatile("st.shared.v2.f32 [%0], {%1, %2};" ::"r"(a), "f"(x), "f"(y) : "memory"); }
__device__ __forceinline__ void sts64(uint32_t a, uint32_t x, uint32_t y) { asm volatile("st.shared.v2.u32 [%0], {%1, %2};" ::"r"(a), "r"(x), "r"(y) : "memory"); }
__device__ __forceinline__ void sts128(uint32_t a, uint32_t x, uint32_t y, uint32_t z, uint32_t w) {
  asm volatile("st.shared.v4.u32 [%0], {%1, %2, %3, %4};" ::"r"(a), "r"(x), "r"(y), "r"(z), "r"(w) : "memory");
}
__device__ __forceinline__ uint32_t lds32(uint32_t a) { uint32_t v; asm volatile("ld.shared.u32 %0, [%1];" : "=r"(v) : "r"(a) : "memory"); return v; }
__device__ __forceinline__ float lds32f(uint32_t a) { float v; asm volatile("ld.shared.f32 %0, [%1];" : "=f"(v) : "r"(a) : "memory"); return v; }
__device__ __forceinline__ float2 lds64f(uint32_t a) { float2 v; asm volatile("ld.shared.v2.f32 {%0, %1}, [%2];" : "=f"(v.x), "=f"(v.y) : "r"(a) : "memory"); return v; }
__device__ __forceinline__ float4 lds128f(uint32_t a) { float4 v; asm volatile("ld.shared.v4.f32 {%0, %1, %2, %3}, [%4];" : "=f"(v.x), "=f"(v.y), "=f"(v.z), "=f"(v.w) : "r"(a) : "memory"); return v; }
__device__ __forceinline__ void ldsm4(uint32_t a, uint32_t& r0, uint32_t& r1, uint32_t& r2, uint32_t& r3) {
  asm volatile("ldmatrix.sync.aligned.m8n8.x4.shared.b16 {%0, %1, %2, %3}, [%4];" : "=r"(r0), "=r"(r1), "=r"(r2), "=r"(r3) : "r"(a) : "memory");
}
__device__ __forceinline__ void ldsm4t(uint32_t a, uint32_t& r0, uint32_t& r1, uint32_t& r2, uint32_t& r3) {
  asm volatile("ldmatrix.sync.aligned.m8n8.x4.trans.shared.b16 {%0, %1, %2, %3}, [%4];" : "=r"(r0), "=r"(r1), "=r"(r2), "=r"(r3) : "r"(a) : "memory");
}
__device__ __forceinline__ void stsm4(uint32_t a, uint32_t r0, uint32_t r1, uint32_t r2, uint32_t r3) {
  asm volatile("stmatrix.sync.aligned.m8n8.x4.shared.b16 [%0], {%1, %2, %3, %4};" ::"r"(a), "r"(r0), "r"(r1), "r"(r2), "r"(r3) : "memory");
}
__device__ __forceinline__ void stsm4t(uint32_t a, uint32_t r0, uint32_t r1, uint32_t r2, uint32_t r3) {
  asm volatile("stmatrix.sync.aligned.m8n8.x4.trans.shared.b16 [%0], {%1, %2, %3, %4};" ::"r"(a), "r"(r0), "r"(r1), "r"(r2), "r"(r3) : "memory");
}
__device__ __forceinline__ void mma16816(float (&d)[4], uint32_t a0, uint32_t a1, uint32_t a2, uint32_t a3, uint32_t b0, uint32_t b1) {
  asm volatile("mma.sync.aligned.m16n8k16.row.col.f32.bf16.bf16.f32 {%0, %1, %2, %3}, {%4, %5, %6, %7}, {%8, %9}, {%0, %1, %2, %3};"
               : "+f"(d[0]), "+f"(d[1]), "+f"(d[2]), "+f"(d[3]) : "r"(a0), "r"(a1), "r"(a2), "r"(a3), "r"(b0), "r"(b1));
}
__device__ __forceinline__ void prefetch_l2_bulk(const void* p, uint32_t bytes) { asm volatile("cp.async.bulk.prefetch.L2.global [%0], %1;" ::"l"(p), "r"(bytes) : "memory"); }
#define TS(slot)
#define TSP(slot)

template <int TA, int TB> __device__ __forceinline__ void wgmma_ss_n24(float (&d)[12], uint64_t da, uint64_t db, int sd) {
  asm volatile("{\n.reg .pred p;\n"
    "setp.ne.b32 p, %14, 0;\n"
    "wgmma.mma_async.sync.aligned.m64n24k16.f32.bf16.bf16 "
    "{%0, %1, %2, %3, %4, %5, %6, %7, %8, %9, %10, %11}, "
    "%12, %13, p, 1, 1, %15, %16;\n}\n"
    : "+f"(d[0]), "+f"(d[1]), "+f"(d[2]), "+f"(d[3]), "+f"(d[4]), "+f"(d[5]), "+f"(d[6]), "+f"(d[7]),
      "+f"(d[8]), "+f"(d[9]), "+f"(d[10]), "+f"(d[11])
    : "l"(da), "l"(db), "r"(sd), "n"(TA), "n"(TB));
}
template <int TA, int TB> __device__ __forceinline__ void wgmma_ss_n40(float (&d)[20], uint64_t da, uint64_t db, int sd) {
  asm volatile("{\n.reg .pred p;\n"
    "setp.ne.b32 p, %22, 0;\n"
    "wgmma.mma_async.sync.aligned.m64n40k16.f32.bf16.bf16 "
    "{%0, %1, %2, %3, %4, %5, %6, %7, %8, %9, %10, %11, %12, %13, %14, %15, "
    "%16, %17, %18, %19}, "
    "%20, %21, p, 1, 1, %23, %24;\n}\n"
    : "+f"(d[0]), "+f"(d[1]), "+f"(d[2]), "+f"(d[3]), "+f"(d[4]), "+f"(d[5]), "+f"(d[6]), "+f"(d[7]),
      "+f"(d[8]), "+f"(d[9]), "+f"(d[10]), "+f"(d[11]), "+f"(d[12]), "+f"(d[13]), "+f"(d[14]), "+f"(d[15]),
      "+f"(d[16]), "+f"(d[17]), "+f"(d[18]), "+f"(d[19])
    : "l"(da), "l"(db), "r"(sd), "n"(TA), "n"(TB));
}
template <int TA, int TB> __device__ __forceinline__ void wgmma_ss_n80(float (&d)[40], uint64_t da, uint64_t db, int sd) {
  asm volatile("{\n.reg .pred p;\n"
    "setp.ne.b32 p, %42, 0;\n"
    "wgmma.mma_async.sync.aligned.m64n80k16.f32.bf16.bf16 "
    "{%0, %1, %2, %3, %4, %5, %6, %7, %8, %9, %10, %11, %12, %13, %14, %15, "
    "%16, %17, %18, %19, %20, %21, %22, %23, %24, %25, %26, %27, %28, %29, %30, %31, "
    "%32, %33, %34, %35, %36, %37, %38, %39}, "
    "%40, %41, p, 1, 1, %43, %44;\n}\n"
    : "+f"(d[0]), "+f"(d[1]), "+f"(d[2]), "+f"(d[3]), "+f"(d[4]), "+f"(d[5]), "+f"(d[6]), "+f"(d[7]),
      "+f"(d[8]), "+f"(d[9]), "+f"(d[10]), "+f"(d[11]), "+f"(d[12]), "+f"(d[13]), "+f"(d[14]), "+f"(d[15]),
      "+f"(d[16]), "+f"(d[17]), "+f"(d[18]), "+f"(d[19]), "+f"(d[20]), "+f"(d[21]), "+f"(d[22]), "+f"(d[23]),
      "+f"(d[24]), "+f"(d[25]), "+f"(d[26]), "+f"(d[27]), "+f"(d[28]), "+f"(d[29]), "+f"(d[30]), "+f"(d[31]),
      "+f"(d[32]), "+f"(d[33]), "+f"(d[34]), "+f"(d[35]), "+f"(d[36]), "+f"(d[37]), "+f"(d[38]), "+f"(d[39])
    : "l"(da), "l"(db), "r"(sd), "n"(TA), "n"(TB));
}
template <int TA, int TB> __device__ __forceinline__ void wgmma_ss_n96(float (&d)[48], uint64_t da, uint64_t db, int sd) {
  asm volatile("{\n.reg .pred p;\n"
    "setp.ne.b32 p, %50, 0;\n"
    "wgmma.mma_async.sync.aligned.m64n96k16.f32.bf16.bf16 "
    "{%0, %1, %2, %3, %4, %5, %6, %7, %8, %9, %10, %11, %12, %13, %14, %15, "
    "%16, %17, %18, %19, %20, %21, %22, %23, %24, %25, %26, %27, %28, %29, %30, %31, "
    "%32, %33, %34, %35, %36, %37, %38, %39, %40, %41, %42, %43, %44, %45, %46, %47}, "
    "%48, %49, p, 1, 1, %51, %52;\n}\n"
    : "+f"(d[0]), "+f"(d[1]), "+f"(d[2]), "+f"(d[3]), "+f"(d[4]), "+f"(d[5]), "+f"(d[6]), "+f"(d[7]),
      "+f"(d[8]), "+f"(d[9]), "+f"(d[10]), "+f"(d[11]), "+f"(d[12]), "+f"(d[13]), "+f"(d[14]), "+f"(d[15]),
      "+f"(d[16]), "+f"(d[17]), "+f"(d[18]), "+f"(d[19]), "+f"(d[20]), "+f"(d[21]), "+f"(d[22]), "+f"(d[23]),
      "+f"(d[24]), "+f"(d[25]), "+f"(d[26]), "+f"(d[27]), "+f"(d[28]), "+f"(d[29]), "+f"(d[30]), "+f"(d[31]),
      "+f"(d[32]), "+f"(d[33]), "+f"(d[34]), "+f"(d[35]), "+f"(d[36]), "+f"(d[37]), "+f"(d[38]), "+f"(d[39]),
      "+f"(d[40]), "+f"(d[41]), "+f"(d[42]), "+f"(d[43]), "+f"(d[44]), "+f"(d[45]), "+f"(d[46]), "+f"(d[47])
    : "l"(da), "l"(db), "r"(sd), "n"(TA), "n"(TB));
}
template <int TA, int TB> __device__ __forceinline__ void wgmma_ss_n192(float (&d)[96], uint64_t da, uint64_t db, int sd) {
  asm volatile("{\n.reg .pred p;\n"
    "setp.ne.b32 p, %98, 0;\n"
    "wgmma.mma_async.sync.aligned.m64n192k16.f32.bf16.bf16 "
    "{%0, %1, %2, %3, %4, %5, %6, %7, %8, %9, %10, %11, %12, %13, %14, %15, "
    "%16, %17, %18, %19, %20, %21, %22, %23, %24, %25, %26, %27, %28, %29, %30, %31, "
    "%32, %33, %34, %35, %36, %37, %38, %39, %40, %41, %42, %43, %44, %45, %46, %47, "
    "%48, %49, %50, %51, %52, %53, %54, %55, %56, %57, %58, %59, %60, %61, %62, %63, "
    "%64, %65, %66, %67, %68, %69, %70, %71, %72, %73, %74, %75, %76, %77, %78, %79, "
    "%80, %81, %82, %83, %84, %85, %86, %87, %88, %89, %90, %91, %92, %93, %94, %95}, "
    "%96, %97, p, 1, 1, %99, %100;\n}\n"
    : "+f"(d[0]), "+f"(d[1]), "+f"(d[2]), "+f"(d[3]), "+f"(d[4]), "+f"(d[5]), "+f"(d[6]), "+f"(d[7]),
      "+f"(d[8]), "+f"(d[9]), "+f"(d[10]), "+f"(d[11]), "+f"(d[12]), "+f"(d[13]), "+f"(d[14]), "+f"(d[15]),
      "+f"(d[16]), "+f"(d[17]), "+f"(d[18]), "+f"(d[19]), "+f"(d[20]), "+f"(d[21]), "+f"(d[22]), "+f"(d[23]),
      "+f"(d[24]), "+f"(d[25]), "+f"(d[26]), "+f"(d[27]), "+f"(d[28]), "+f"(d[29]), "+f"(d[30]), "+f"(d[31]),
      "+f"(d[32]), "+f"(d[33]), "+f"(d[34]), "+f"(d[35]), "+f"(d[36]), "+f"(d[37]), "+f"(d[38]), "+f"(d[39]),
      "+f"(d[40]), "+f"(d[41]), "+f"(d[42]), "+f"(d[43]), "+f"(d[44]), "+f"(d[45]), "+f"(d[46]), "+f"(d[47]),
      "+f"(d[48]), "+f"(d[49]), "+f"(d[50]), "+f"(d[51]), "+f"(d[52]), "+f"(d[53]), "+f"(d[54]), "+f"(d[55]),
      "+f"(d[56]), "+f"(d[57]), "+f"(d[58]), "+f"(d[59]), "+f"(d[60]), "+f"(d[61]), "+f"(d[62]), "+f"(d[63]),
      "+f"(d[64]), "+f"(d[65]), "+f"(d[66]), "+f"(d[67]), "+f"(d[68]), "+f"(d[69]), "+f"(d[70]), "+f"(d[71]),
      "+f"(d[72]), "+f"(d[73]), "+f"(d[74]), "+f"(d[75]), "+f"(d[76]), "+f"(d[77]), "+f"(d[78]), "+f"(d[79]),
      "+f"(d[80]), "+f"(d[81]), "+f"(d[82]), "+f"(d[83]), "+f"(d[84]), "+f"(d[85]), "+f"(d[86]), "+f"(d[87]),
      "+f"(d[88]), "+f"(d[89]), "+f"(d[90]), "+f"(d[91]), "+f"(d[92]), "+f"(d[93]), "+f"(d[94]), "+f"(d[95])
    : "l"(da), "l"(db), "r"(sd), "n"(TA), "n"(TB));
}
template <int TA, int TB> __device__ __forceinline__ void wgmma_ss_n240(float (&d)[120], uint64_t da, uint64_t db, int sd) {
  asm volatile("{\n.reg .pred p;\n"
    "setp.ne.b32 p, %122, 0;\n"
    "wgmma.mma_async.sync.aligned.m64n240k16.f32.bf16.bf16 "
    "{%0, %1, %2, %3, %4, %5, %6, %7, %8, %9, %10, %11, %12, %13, %14, %15, "
    "%16, %17, %18, %19, %20, %21, %22, %23, %24, %25, %26, %27, %28, %29, %30, %31, "
    "%32, %33, %34, %35, %36, %37, %38, %39, %40, %41, %42, %43, %44, %45, %46, %47, "
    "%48, %49, %50, %51, %52, %53, %54, %55, %56, %57, %58, %59, %60, %61, %62, %63, "
    "%64, %65, %66, %67, %68, %69, %70, %71, %72, %73, %74, %75, %76, %77, %78, %79, "
    "%80, %81, %82, %83, %84, %85, %86, %87, %88, %89, %90, %91, %92, %93, %94, %95, "
    "%96, %97, %98, %99, %100, %101, %102, %103, %104, %105, %106, %107, %108, %109, %110, %111, "
    "%112, %113, %114, %115, %116, %117, %118, %119}, "
    "%120, %121, p, 1, 1, %123, %124;\n}\n"
    : "+f"(d[0]), "+f"(d[1]), "+f"(d[2]), "+f"(d[3]), "+f"(d[4]), "+f"(d[5]), "+f"(d[6]), "+f"(d[7]),
      "+f"(d[8]), "+f"(d[9]), "+f"(d[10]), "+f"(d[11]), "+f"(d[12]), "+f"(d[13]), "+f"(d[14]), "+f"(d[15]),
      "+f"(d[16]), "+f"(d[17]), "+f"(d[18]), "+f"(d[19]), "+f"(d[20]), "+f"(d[21]), "+f"(d[22]), "+f"(d[23]),
      "+f"(d[24]), "+f"(d[25]), "+f"(d[26]), "+f"(d[27]), "+f"(d[28]), "+f"(d[29]), "+f"(d[30]), "+f"(d[31]),
      "+f"(d[32]), "+f"(d[33]), "+f"(d[34]), "+f"(d[35]), "+f"(d[36]), "+f"(d[37]), "+f"(d[38]), "+f"(d[39]),
      "+f"(d[40]), "+f"(d[41]), "+f"(d[42]), "+f"(d[43]), "+f"(d[44]), "+f"(d[45]), "+f"(d[46]), "+f"(d[47]),
      "+f"(d[48]), "+f"(d[49]), "+f"(d[50]), "+f"(d[51]), "+f"(d[52]), "+f"(d[53]), "+f"(d[54]), "+f"(d[55]),
      "+f"(d[56]), "+f"(d[57]), "+f"(d[58]), "+f"(d[59]), "+f"(d[60]), "+f"(d[61]), "+f"(d[62]), "+f"(d[63]),
      "+f"(d[64]), "+f"(d[65]), "+f"(d[66]), "+f"(d[67]), "+f"(d[68]), "+f"(d[69]), "+f"(d[70]), "+f"(d[71]),
      "+f"(d[72]), "+f"(d[73]), "+f"(d[74]), "+f"(d[75]), "+f"(d[76]), "+f"(d[77]), "+f"(d[78]), "+f"(d[79]),
      "+f"(d[80]), "+f"(d[81]), "+f"(d[82]), "+f"(d[83]), "+f"(d[84]), "+f"(d[85]), "+f"(d[86]), "+f"(d[87]),
      "+f"(d[88]), "+f"(d[89]), "+f"(d[90]), "+f"(d[91]), "+f"(d[92]), "+f"(d[93]), "+f"(d[94]), "+f"(d[95]),
      "+f"(d[96]), "+f"(d[97]), "+f"(d[98]), "+f"(d[99]), "+f"(d[100]), "+f"(d[101]), "+f"(d[102]), "+f"(d[103]),
      "+f"(d[104]), "+f"(d[105]), "+f"(d[106]), "+f"(d[107]), "+f"(d[108]), "+f"(d[109]), "+f"(d[110]), "+f"(d[111]),
      "+f"(d[112]), "+f"(d[113]), "+f"(d[114]), "+f"(d[115]), "+f"(d[116]), "+f"(d[117]), "+f"(d[118]), "+f"(d[119])
    : "l"(da), "l"(db), "r"(sd), "n"(TA), "n"(TB));
}

template <int N> __device__ __forceinline__ void fence_regs(float (&a)[N]) {
#pragma unroll
  for (int i = 0; i < N; i++) asm volatile("" : "+f"(a[i])::"memory");
}
template <int N> struct WG;
template <> struct WG<240> { static __device__ __forceinline__ void mma(float (&d)[120], uint64_t a, uint64_t b, int sd) { wgmma_ss_n240<0, 0>(d, a, b, sd); } };
template <> struct WG<192> { static __device__ __forceinline__ void mma(float (&d)[96], uint64_t a, uint64_t b, int sd) { wgmma_ss_n192<0, 0>(d, a, b, sd); } };
template <> struct WG<96> { static __device__ __forceinline__ void mma(float (&d)[48], uint64_t a, uint64_t b, int sd) { wgmma_ss_n96<0, 0>(d, a, b, sd); } };
template <> struct WG<80> { static __device__ __forceinline__ void mma(float (&d)[40], uint64_t a, uint64_t b, int sd) { wgmma_ss_n80<0, 0>(d, a, b, sd); } };

template <int BN, int SLOTS, uint32_t SLOTB, int KB, bool BRES, int BOFF>
__device__ __forceinline__ void mainloop(float (&acc)[BN / 2], int nit, uint32_t sb, uint32_t boff, int poff, int wg, bool elect, uint32_t& ph, int tsslot,
                                         uint32_t pbf = 0) {
  const uint32_t bars = sb + SM_BARS;
  const uint64_t da0 = desc_k128(sb + wg * 8192), db0 = desc_k128(sb + boff);
  int s = poff, bi = BOFF, bp = BOFF, bpair = 1, i = 0;
#pragma unroll
  for (int k = 0; k < BN / 2; k++) acc[k] = 0.f;
  fence_regs(acc);
#pragma unroll 1
  for (int it = 0; it < nit; it++) {
    if (BRES && (it & ~2) == 0) mbar_wait(bars + (it == 0 ? B_BFULL : B_BFULL1), pbf);
    if (SLEEPNS > 0 && it == 0) mbar_wait_long<SLEEPNS>(bars + B_FULL + 8 * bi, (ph >> bi) & 1);
    else mbar_wait(bars + B_FULL + 8 * bi, (ph >> bi) & 1);
    ph ^= 1u << bi;
    if (it == 0) TS(tsslot);
    const uint64_t da = da0 + (uint64_t)(s * (SLOTB >> 4));
    const uint64_t db = BRES ? db0 + (uint64_t)(bpair * (KB * 10240 >> 4)) : db0 + (uint64_t)(s * (SLOTB >> 4));
    wgmma_fence();
#pragma unroll
    for (int g = 0; g < KB; g++)
#pragma unroll
      for (int k = 0; k < 4; k++) WG<BN>::mma(acc, da + g * (16384 >> 4) + 2 * k, db + g * (10240 >> 4) + 2 * k, 1);
    wgmma_commit();
    wgmma_wait<1>();
    if (it > 0 && elect) mbar_arrive(bars + B_EMPTY + 8 * bp);
    bp = bi;
    s = (s + 1 == SLOTS) ? 0 : s + 1;
    if (BRES) bpair = (bpair == 4) ? 0 : bpair + 1;
    if (BOFF == 0) bi = s;
    else { i = (i + 1 == SLOTS) ? 0 : i + 1; bi = (i + BOFF >= 7) ? i + BOFF - 7 : i + BOFF; }
  }
  wgmma_wait<0>();
  fence_regs(acc);
  if (elect) { mbar_arrive(bars + B_EMPTY + 8 * bp); mbar_arrive(bars + B_MMADONE); }
}

template <int NV>
__device__ __forceinline__ void row_partial_stats(const float (&v)[NV], float inv_n, float& mean, float& m2) {
  float s0 = 0.f, s1 = 0.f, s2 = 0.f, s3 = 0.f;
#pragma unroll
  for (int i = 0; i < NV; i += 4) { s0 += v[i]; s1 += v[i + 1]; s2 += v[i + 2]; s3 += v[i + 3]; }
  float s = (s0 + s1) + (s2 + s3);
  s += __shfl_xor_sync(0xffffffffu, s, 1);
  s += __shfl_xor_sync(0xffffffffu, s, 2);
  mean = s * inv_n;
  float q0 = 0.f, q1 = 0.f, q2 = 0.f, q3 = 0.f;
#pragma unroll
  for (int i = 0; i < NV; i += 4) {
    const float d0 = v[i] - mean, d1 = v[i + 1] - mean, d2 = v[i + 2] - mean, d3 = v[i + 3] - mean;
    q0 = fmaf(d0, d0, q0); q1 = fmaf(d1, d1, q1); q2 = fmaf(d2, d2, q2); q3 = fmaf(d3, d3, q3);
  }
  float q = (q0 + q1) + (q2 + q3);
  q += __shfl_xor_sync(0xffffffffu, q, 1);
  q += __shfl_xor_sync(0xffffffffu, q, 2);
  m2 = q;
}

template <int NB, int NW, bool CS>
__device__ __forceinline__ void transpose_item(uint32_t raw, uint32_t img, int row0, uint32_t cs, int warp, int lane) {
#pragma unroll 1
  for (int nb = warp; nb < NB / 8; nb += NW) {
    float sum = 0.f;
#pragma unroll
    for (int t = 0; t < 2; t++) {
      uint32_t r0, r1, r2, r3;
      ldsm4t(raw + (8 * (4 * t + (lane >> 3)) + (lane & 7)) * (2 * NB) + nb * 16, r0, r1, r2, r3);
      const int n = row0 + 8 * nb + (lane & 7), c = 4 * t + (lane >> 3);
      stsm4(img + n * 128 + ((c ^ (n & 7)) << 4), r0, r1, r2, r3);
      if (CS) sum += ((bf_lo(r0) + bf_hi(r0)) + (bf_lo(r1) + bf_hi(r1))) + ((bf_lo(r2) + bf_hi(r2)) + (bf_lo(r3) + bf_hi(r3)));
    }
    if (CS) {
      sum += __shfl_xor_sync(0xffffffffu, sum, 1);
      sum += __shfl_xor_sync(0xffffffffu, sum, 2);
      if ((lane & 3) == 0) asm volatile("st.shared.f32 [%0], %1;" ::"r"(cs + (row0 + 8 * nb + (lane >> 2)) * 4), "f"(sum) : "memory");
    }
  }
}

constexpr uint32_t P0_PHIR = 16384, P0_PHIT = 20480, P0_CS = 32768, P0_CS2 = 34816, P0_ZERO = 36864;
constexpr uint32_t P0_RAW0 = 47104 + 16384, P0_IMG0 = 2 * 47104 + 16384;
constexpr uint32_t P0_RAW1 = 3 * 47104, P0_IMG1 = 3 * 47104 + 24576, P0_CS3 = 3 * 47104 + 49152;

__device__ __forceinline__ void prologue_issue_stage1(const Params& p, uint32_t sb, int b, int j, int row0) {
  const uint32_t bars = sb + SM_BARS;
  mbar_expect_tx(bars + B_XT, 20480);
  tma_ld(sb + SM_XT, &p.tmAx80, 80 * j, row0, bars + B_XT);
  if (b < 80) {
    mbar_expect_tx(bars + B_RAW1, 20480);
    tma_ld(sb + P0_RAW1, &p.tmWo, 80 * (b / 10), 64 * (b % 10), bars + B_RAW1);
    tma_ld(sb + P0_RAW1 + 10240, &p.tmWout, 80 * (b / 12), 64 * (b % 12), bars + B_RAW1);
  } else if (b < 112) {
    const int i1 = b - 80 + 48, j1 = i1 / 10, k1 = i1 % 10;
    mbar_expect_tx(bars + B_RAW1, 24576);
    tma_ld(sb + P0_RAW1, &p.tmWi, 768 + 96 * j1, 64 * k1, bars + B_RAW1);
    tma_ld(sb + P0_RAW1 + 12288, &p.tmWi, 96 * j1, 64 * k1, bars + B_RAW1);
  } else {
    const int io = 80 + (b - 112);
    mbar_expect_tx(bars + B_RAW1, 10240);
    tma_ld(sb + P0_RAW1, &p.tmWout, 80 * (io / 12), 64 * (io % 12), bars + B_RAW1);
  }
}

__device__ __forceinline__ void prologue_stage0(const Params& p, uint32_t sb, int b, int j, int row0, int tid, int warp, int lane, uint32_t cnt) {
  const uint32_t bars = sb + SM_BARS;
  const bool clsA = b < 80;
  const int q = lane & 3, rw = lane >> 2, khalf = warp & 1;
  if (clsA) {
    for (int i = tid; i < 5 * 32 * 18; i += NTHREADS) sts32(sb + P0_PHIT + i * 4, 0);
    for (int i = tid; i < 384; i += NTHREADS) sts32(sb + P0_ZERO + i * 4, 0);
    __syncthreads();
    mbar_wait(bars + B_PHI, 0);
#pragma unroll
    for (int it = 0; it < 5; it++) {
      const int i = tid + it * NTHREADS;
      if (i < 1600) {
        const int h = i / 400, d = (i % 400) / 20, e = i % 20;
        uint16_t v;
        asm volatile("ld.shared.u16 %0, [%1];" : "=h"(v) : "r"(sb + P0_PHIR + i * 2) : "memory");
        asm volatile("st.shared.u16 [%0], %1;" ::"r"(sb + P0_PHIT + h * 2304 + e * 72 + d * 2), "h"(v) : "memory");
      } else if (i < 1620) {
        const int e = i - 1600;
        asm volatile("st.shared.u16 [%0], %1;" ::"r"(sb + P0_PHIT + 4 * 2304 + e * 72 + e * 2), "h"((uint16_t)0x3f80) : "memory");
      }
    }
    asm volatile("cp.async.wait_all;" ::: "memory");
    __syncthreads();
    TS(114);
#pragma unroll
    for (int rep = 0; rep < 2; rep++) {
      const int combo = (warp + 12 * rep) >> 1, part = combo >> 2, hh = combo & 3;
      const uint32_t pa = sb + P0_PHIT + (part == 2 ? 4 : hh) * 2304;
      uint32_t a[2][2][4];
#pragma unroll
      for (int mt = 0; mt < 2; mt++)
#pragma unroll
        for (int ks = 0; ks < 2; ks++) {
          const uint32_t base = pa + (16 * mt + rw) * 72 + (16 * ks + 2 * q) * 2;
          a[mt][ks][0] = lds32(base); a[mt][ks][1] = lds32(base + 8 * 72); a[mt][ks][2] = lds32(base + 16); a[mt][ks][3] = lds32(base + 8 * 72 + 16);
        }
      float cs[3] = {0.f, 0.f, 0.f};
      const int n0 = 8 * (10 * part + (rw >> 1)) + 2 * hh + (rw & 1);
      const uint32_t ib = sb + P0_IMG0 + n0 * 128 + q * 4;
      const uint32_t rb0 = sb + P0_RAW0 + part * 10240 + (32 * khalf + rw) * 160 + (20 * hh + 2 * q) * 2;
      uint32_t b0[4], b1[4], b2[4];
#pragma unroll
      for (int nt = 0; nt < 4; nt++) {
        b0[nt] = lds32(rb0 + nt * 1280); b1[nt] = lds32(rb0 + nt * 1280 + 16); b2[nt] = (q < 2) ? lds32(rb0 + nt * 1280 + 32) : 0u;
      }
#pragma unroll
      for (int nt = 0; nt < 4; nt++) {
        float d0[4] = {0.f, 0.f, 0.f, 0.f}, d1[4] = {0.f, 0.f, 0.f, 0.f};
        mma16816(d0, a[0][0][0], a[0][0][1], a[0][0][2], a[0][0][3], b0[nt], b1[nt]);
        mma16816(d1, a[1][0][0], a[1][0][1], a[1][0][2], a[1][0][3], b0[nt], b1[nt]);
        mma16816(d0, a[0][1][0], a[0][1][1], a[0][1][2], a[0][1][3], b2[nt], 0u);
        mma16816(d1, a[1][1][0], a[1][1][1], a[1][1][2], a[1][1][3], b2[nt], 0u);
        const uint32_t sw = ((4 * khalf + nt) ^ (n0 & 7)) << 4;
        const uint32_t w0 = pack_bf16(d0[0], d0[1]), w1 = pack_bf16(d0[2], d0[3]), w2 = pack_bf16(d1[0], d1[1]);
        sts32(ib + sw, w0); cs[0] += bf_lo(w0) + bf_hi(w0);
        sts32(ib + 32 * 128 + sw, w1); cs[1] += bf_lo(w1) + bf_hi(w1);
        if (rw < 4) { sts32(ib + 64 * 128 + sw, w2); cs[2] += bf_lo(w2) + bf_hi(w2); }
      }
#pragma unroll
      for (int i = 0; i < 3; i++) {
        cs[i] += __shfl_xor_sync(0xffffffffu, cs[i], 1);
        cs[i] += __shfl_xor_sync(0xffffffffu, cs[i], 2);
        if (q == 0 && rw + 8 * i < 20)
          asm volatile("st.shared.f32 [%0], %1;" ::"r"(sb + P0_CS + (khalf * 240 + n0 + 32 * i) * 4), "f"(cs[i]) : "memory");
      }
    }
    __syncthreads();
    if (tid < 240) {
      const float v = lds32f(sb + P0_CS + tid * 4) + lds32f(sb + P0_CS + (240 + tid) * 4);
      asm volatile("st.shared.f32 [%0], %1;" ::"r"(sb + P0_CS2 + tid * 4), "f"(v) : "memory");
    }
  } else {
    mbar_wait(bars + B_RAW0, 0);
    TS(114);
    transpose_item<96, 12, true>(sb + P0_RAW0, sb + P0_IMG0, 0, sb + P0_CS2, warp, lane);
    transpose_item<96, 12, true>(sb + P0_RAW0 + 12288, sb + P0_IMG0, 96, sb + P0_CS2, warp, lane);
  }
  if (tid == 0) sts32(sb + SM_ZMASK + 8, (cnt >> 7) + 1);
  fence_async_smem();
  __syncthreads();
}

__device__ __forceinline__ void prologue_stage1(uint32_t sb, int b, int warp, int lane, uint4* xstat, uint32_t tag) {
  const uint32_t bars = sb + SM_BARS;
  mbar_wait(bars + B_XT, 0);
#pragma unroll
  for (int h = 0; h < 2; h++) {
    float v[20];
#pragma unroll
    for (int jj = 0; jj < 10; jj++) {
      const uint32_t x = lds32(sb + SM_XT + (16 * warp + 8 * h + (lane >> 2)) * 160 + jj * 16 + (lane & 3) * 4);
      v[2 * jj] = bf_lo(x); v[2 * jj + 1] = bf_hi(x);
    }
    float mean, m2;
    row_partial_stats<20>(v, 1.f / 80.f, mean, m2);
    if ((lane & 3) == 0) st_tagged(xstat + 16 * warp + 8 * h + (lane >> 2), mean, m2, tag);
  }
  if (lane == 0) mbar_arrive(bars + B_XSLOC);
  mbar_wait(bars + B_RAW1, 0);
  if (b < 80) {
    transpose_item<80, 8, false>(sb + P0_RAW1, sb + P0_IMG1, 0, 0, warp, lane);
    transpose_item<80, 8, false>(sb + P0_RAW1 + 10240, sb + P0_IMG1 + 10240, 0, 0, warp, lane);
  } else if (b < 112) {
    transpose_item<96, 8, true>(sb + P0_RAW1, sb + P0_IMG1, 0, sb + P0_CS3, warp, lane);
    transpose_item<96, 8, true>(sb + P0_RAW1 + 12288, sb + P0_IMG1, 96, sb + P0_CS3, warp, lane);
  } else {
    transpose_item<80, 8, false>(sb + P0_RAW1, sb + P0_IMG1, 0, 0, warp, lane);
  }
  fence_async_smem(); __syncwarp();
  if (lane == 0) mbar_arrive(bars + B_STGO);
}

template <bool ZPAD>
__device__ __forceinline__ void feature_map2(const float (&w0)[20], const float (&w1)[20], float s0, float s1, uint32_t dst) {
  float mx[2][2], mn[2][2];
#pragma unroll
  for (int c = 0; c < 2; c++) {
    mx[0][c] = fmaxf(w0[c], w0[c + 2]); mn[0][c] = fminf(w0[c], w0[c + 2]);
    mx[1][c] = fmaxf(w1[c], w1[c + 2]); mn[1][c] = fminf(w1[c], w1[c + 2]);
  }
#pragma unroll
  for (int i = 4; i < 20; i++) {
    mx[0][i & 1] = fmaxf(mx[0][i & 1], w0[i]); mn[0][i & 1] = fminf(mn[0][i & 1], w0[i]);
    mx[1][i & 1] = fmaxf(mx[1][i & 1], w1[i]); mn[1][i & 1] = fminf(mn[1][i & 1], w1[i]);
  }
  const float a0 = -s0 * fmaxf(mx[0][0], mx[0][1]), b0 = s0 * fminf(mn[0][0], mn[0][1]);
  const float a1 = -s1 * fmaxf(mx[1][0], mx[1][1]), b1 = s1 * fminf(mn[1][0], mn[1][1]);
#pragma unroll
  for (int half = 0; half < 2; half++) {
    const float m0 = half ? -s0 : s0, m1 = half ? -s1 : s1, c0 = half ? b0 : a0, c1 = half ? b1 : a1;
    float e0[20], e1[20], t0[2] = {0.f, 0.f}, t1[2] = {0.f, 0.f};
#pragma unroll
    for (int i = 0; i < 20; i++) {
      e0[i] = ex2(fmaf(w0[i], m0, c0)); t0[i & 1] += e0[i];
      e1[i] = ex2(fmaf(w1[i], m1, c1)); t1[i & 1] += e1[i];
    }
    const float r0 = rcp(t0[0] + t0[1]), r1 = rcp(t1[0] + t1[1]);
    uint32_t o0[10], o1[10];
#pragma unroll
    for (int i = 0; i < 10; i++) { o0[i] = pack_bf16(e0[2 * i] * r0, e0[2 * i + 1] * r0); o1[i] = pack_bf16(e1[2 * i] * r1, e1[2 * i + 1] * r1); }
    if (half == 0) {
      sts128(dst, o0[0], o0[1], o0[2], o0[3]); sts128(dst + 128, o1[0], o1[1], o1[2], o1[3]);
      sts128(dst + 2048, o0[4], o0[5], o0[6], o0[7]); sts128(dst + 2048 + 128, o1[4], o1[5], o1[6], o1[7]);
      sts64(dst + 4096, o0[8], o0[9]); sts64(dst + 4096 + 128, o1[8], o1[9]);
    } else {
      sts64(dst + 4096 + 8, o0[0], o0[1]); sts64(dst + 4096 + 128 + 8, o1[0], o1[1]);
      sts128(dst + 6144, o0[2], o0[3], o0[4], o0[5]); sts128(dst + 6144 + 128, o1[2], o1[3], o1[4], o1[5]);
      sts128(dst + 8192, o0[6], o0[7], o0[8], o0[9]); sts128(dst + 8192 + 128, o1[6], o1[7], o1[8], o1[9]);
    }
  }
  if (ZPAD) { sts128(dst + 10240, 0u, 0u, 0u, 0u); sts128(dst + 10240 + 128, 0u, 0u, 0u, 0u); }
}

__device__ __forceinline__ uint32_t residual_addr(uint32_t sb, int wg, int w, int lane) {
  return sb + SM_XT + (64 * wg + 16 * w + 8 * ((lane >> 3) & 1) + (lane & 7)) * 160 + (lane >> 4) * 16;
}
__device__ __forceinline__ void residual_load(uint32_t (&r)[5][4], uint32_t rowa) {
#pragma unroll
  for (int t = 0; t < 5; t++) ldsm4(rowa + t * 32, r[t][0], r[t][1], r[t][2], r[t][3]);
}
__device__ __forceinline__ void residual_update(const float (&acc)[40], uint32_t (&r)[5][4], float (&v)[2][20], uint32_t rowa) {
#pragma unroll
  for (int t = 0; t < 5; t++) {
#pragma unroll
    for (int m = 0; m < 4; m++) {
      const int h = m & 1, jj = 2 * t + (m >> 1);
      r[t][m] = pack_bf16(bf_lo(r[t][m]) + acc[4 * jj + 2 * h], bf_hi(r[t][m]) + acc[4 * jj + 2 * h + 1]);
      v[h][2 * jj] = bf_lo(r[t][m]); v[h][2 * jj + 1] = bf_hi(r[t][m]);
    }
    stsm4(rowa + t * 32, r[t][0], r[t][1], r[t][2], r[t][3]);
  }
}

__device__ __forceinline__ void combine_stats(const float2 (&pt)[8], float n, float& mean, float& rstd) {
  float m = 0.f;
#pragma unroll
  for (int i = 0; i < 8; i++) m += pt[i].x;
  m *= 0.125f;
  float m2 = 0.f;
#pragma unroll
  for (int i = 0; i < 8; i++) { const float d = pt[i].x - m; m2 += fmaf(n * d, d, pt[i].y); }
  mean = m;
  rstd = rsqrtf(m2 / (8.f * n) + 1e-5f);
}

__device__ __forceinline__ float gelu_half(float hy) {
  const float u = hy * fmaf(hy * hy, 8.f * 0.044715f * 0.7978845608028654f, 2.f * 0.7978845608028654f);
  return fmaf(hy, tanh_fast(u), hy);
}

__global__ void __launch_bounds__(NTHREADS, 1) fused_kernel(const __grid_constant__ Params p) {
  extern __shared__ __align__(1024) uint8_t smem_raw[];
  const uint32_t sb = smem_u32(smem_raw);
  const uint32_t bars = sb + SM_BARS;
  const int tid = threadIdx.x, warp = __shfl_sync(0xffffffffu, tid >> 5, 0), lane = tid & 31;
  const int b = blockIdx.x, r = b >> 3, j = b & 7;
  const int row0 = r * 128;
  trap_if((sb & 1023) != 0);
  TS(0);
  if (b < 80) {
    const uint8_t* src = reinterpret_cast<const uint8_t*>(p.wqkv) + (size_t)(64 * (b % 10)) * 3840 + (b / 10) * 160;
#pragma unroll
    for (int i = 0; i < 5; i++) {
      const int c = tid + i * NTHREADS, part = c / 640, k = (c % 640) / 10, ch = c % 10;
      asm volatile("cp.async.cg.shared.global [%0], [%1], 16;" ::"r"(sb + P0_RAW0 + part * 10240 + k * 160 + ch * 16),
                   "l"(src + (size_t)k * 3840 + part * 1280 + ch * 16) : "memory");
    }
    asm volatile("cp.async.commit_group;" ::: "memory");
  }

  if (warp == 8) {
    if (elect_one()) {
      sts32(sb + SM_ZMASK, 0); sts32(sb + SM_ZMASK + 4, 0);
#pragma unroll 1
      for (int s = 0; s < 7; s++) { mbar_init(bars + B_FULL + 8 * s, 1); mbar_init(bars + B_EMPTY + 8 * s, 2); }
      mbar_init(bars + B_MMADONE, 2);
      mbar_init(bars + B_BFULL, 1); mbar_init(bars + B_BFULL1, 1); mbar_init(bars + B_XT, 1); mbar_init(bars + B_RAW0, 1); mbar_init(bars + B_XSFULL, 2);
      mbar_init(bars + B_STGFREE, 1); mbar_init(bars + B_RAW1, 1); mbar_init(bars + B_STGO, 8); mbar_init(bars + B_STGO + 8, 8);
      mbar_init(bars + B_P0A, 1); mbar_init(bars + B_P0B, 1); mbar_init(bars + B_PHI, 1); mbar_init(bars + B_XSLOC, 8); mbar_init(bars + B_ZNLOC, 1);
      fence_async_smem();
      if (b < 80) {
        mbar_expect_tx(bars + B_PHI, 3200);
        bulk_ld(sb + P0_PHIR, p.wphi + (b / 10) * 1600, 3200, bars + B_PHI);
      } else {
        const int i0 = b - 80, j0 = i0 / 10, k0 = i0 % 10;
        mbar_expect_tx(bars + B_RAW0, 24576);
        tma_ld(sb + P0_RAW0, &p.tmWi, 768 + 96 * j0, 64 * k0, bars + B_RAW0);
        tma_ld(sb + P0_RAW0 + 12288, &p.tmWi, 96 * j0, 64 * k0, bars + B_RAW0);
      }
#pragma unroll 1
      for (int s = 0; s < 3; s++) {
        mbar_expect_tx(bars + B_FULL + 8 * (3 + s), 16384 + 30720);
        tma_ld(sb + s * 47104, &p.tmAx64, s * 64, row0, bars + B_FULL + 8 * (3 + s));
      }
      prologue_issue_stage1(p, sb, b, j, row0);
    }
    __syncwarp();
  }
  uint32_t cnt = 0;
  if (tid == 0) asm volatile("atom.relaxed.gpu.global.add.u32 %0, [%1], 1;" : "=r"(cnt) : "l"(g_flags + F_CNT * 32) : "memory");
  __syncthreads();
  prologue_stage0(p, sb, b, j, row0, tid, warp, lane, cnt);
  const uint32_t e1 = lds32(sb + SM_ZMASK + 8);
  TS(1);

  if (warp >= 8) {
    asm volatile("setmaxnreg.dec.sync.aligned.u32 88;");
    if (warp == 8) {
      if (elect_one()) {
        uint32_t ph = 0, pmma = 0, pstg = 0;
        auto peek = [&](int s) { mbar_wait(bars + B_EMPTY + 8 * s, ((ph >> s) & 1) ^ 1); };
        auto acquire = [&](int s, uint32_t bytes) { peek(s); ph ^= 1u << s; mbar_expect_tx(bars + B_FULL + 8 * s, bytes); };
        const uint8_t* wb = g_wqkv + (size_t)j * 10 * 30720;
        const uint8_t* wi = g_win + (size_t)j * 10 * 24576;
        const uint8_t* wo = g_wo + (size_t)j * 102400;
        const uint8_t* wz = g_wout + (size_t)j * 122880;
#pragma unroll 1
        for (int layer = 0; layer < 2; layer++) {
          const CUtensorMap* tmx = layer == 0 ? &p.tmAx64 : &p.tmX64;
          const int xrow = row0 + (layer == 0 ? 0 : S_);
          int s;
          if (layer == 0) {
            ph |= 7u << 3;
            mbar_wait(bars + B_P0A, 0);
            wait_flag(g_flags + (F_WQ + j) * 32, e1 * 10);
            TSP(2);
#pragma unroll 1
            for (s = 0; s < 3; s++) bulk_ld(sb + s * 47104 + 16384, wb + (size_t)s * 30720, 30720, bars + B_FULL + 8 * (3 + s));
            mbar_wait(bars + B_P0B, 0);
            acquire(6, 16384 + 30720);
            tma_ld(sb + 3 * 47104, tmx, 3 * 64, xrow, bars + B_FULL + 48);
            bulk_ld(sb + 3 * 47104 + 16384, wb + (size_t)3 * 30720, 30720, bars + B_FULL + 48);
          } else {
#pragma unroll 1
            for (s = 1; s < 4; s++) acquire(3 + s, 16384 + 30720);
            wait_flag(g_flags + (F_X2 + r) * 32, e1 * 8);
            TSP(69 + layer * 24);
            tma_ld(sb + 3 * 47104, tmx, 0, xrow, bars + B_FULL + 24);
#pragma unroll
            for (s = 1; s < 4; s++) {
              tma_ld(sb + (s - 1) * 47104, tmx, s * 64, xrow, bars + B_FULL + 8 * (3 + s));
              bulk_ld(sb + (s - 1) * 47104 + 16384, wb + (size_t)s * 30720, 30720, bars + B_FULL + 8 * (3 + s));
            }
          }
#pragma unroll 1
          for (int kb = 4; kb < 10; kb++) {
            const int i = kb & 3, ps = (i + 3 * layer) & 3;
            acquire(3 + i, 16384 + 30720);
            tma_ld(sb + ps * 47104, tmx, kb * 64, xrow, bars + B_FULL + 8 * (3 + i));
            bulk_ld(sb + ps * 47104 + 16384, wb + (size_t)kb * 30720, 30720, bars + B_FULL + 8 * (3 + i));
          }
          mbar_wait(bars + B_MMADONE, pmma); pmma ^= 1;
          if (layer == 0) wait_flag(g_flags + F_WREST * 32, e1 * 128);
          mbar_expect_tx(bars + B_BFULL, 40960);
          bulk_ld(sb + SM_WO + 20480, wo, 40960, bars + B_BFULL);
          mbar_expect_tx(bars + B_BFULL1, 61440);
          bulk_ld(sb + SM_WO + 61440, wo + 40960, 40960, bars + B_BFULL1);
          bulk_ld(sb + SM_WO, wo + 81920, 20480, bars + B_BFULL1);
#pragma unroll 1
          for (s = 0; s < 3; s++) acquire(s, 32768);
          wait_flag(g_flags + (F_O + layer * 16 + r) * 32, e1 * 8);
          TSP(70 + layer * 24);
#pragma unroll
          for (int kb = 0; kb < 6; kb++) tma_ld(sb + kb * 16384, &p.tmO64, kb * 64, row0, bars + B_FULL + 8 * (kb >> 1));
#pragma unroll 1
          for (s = 0; s < 2; s++) {
            acquire(s, 32768);
            tma_ld(sb + s * 32768, &p.tmO64, (2 * s + 6) * 64, row0, bars + B_FULL + 8 * s);
            tma_ld(sb + s * 32768 + 16384, &p.tmO64, (2 * s + 7) * 64, row0, bars + B_FULL + 8 * s);
          }
          acquire(3, 16384 + 24576);
          bulk_ld(sb + 3 * 40960 + 16384, wi, 24576, bars + B_FULL + 24);
          peek(0);
          acquire(4, 16384 + 24576);
          bulk_ld(sb + 4 * 40960 + 16384, wi + 24576, 24576, bars + B_FULL + 32);
          mbar_wait(bars + B_MMADONE, pmma); pmma ^= 1;
          acquire(5, 16384 + 24576); acquire(6, 16384 + 24576); acquire(0, 16384 + 24576);
          wait_flag(g_flags + (F_X1 + layer * 16 + r) * 32, e1 * 8);
          TSP(71 + layer * 24);
          const int x1row = row0 + (layer == 0 ? 0 : 2 * S_);
          tma_ld(sb + 3 * 40960, &p.tmX64, 0, x1row, bars + B_FULL + 24);
          tma_ld(sb + 4 * 40960, &p.tmX64, 64, x1row, bars + B_FULL + 32);
#pragma unroll
          for (s = 0; s < 3; s++) {
            const uint32_t fb = bars + B_FULL + 8 * (s == 2 ? 0 : 5 + s);
            tma_ld(sb + s * 40960, &p.tmX64, (s + 2) * 64, x1row, fb);
            bulk_ld(sb + s * 40960 + 16384, wi + (size_t)(s + 2) * 24576, 24576, fb);
          }
#pragma unroll 1
          for (int i = 0; i < 5; i++) {
            const int bi = i == 4 ? 0 : 3 + i, ps = i < 2 ? i + 3 : i - 2;
            acquire(bi, 16384 + 24576);
            tma_ld(sb + ps * 40960, &p.tmX64, (i + 5) * 64, x1row, bars + B_FULL + 8 * bi);
            bulk_ld(sb + ps * 40960 + 16384, wi + (size_t)(i + 5) * 24576, 24576, bars + B_FULL + 8 * bi);
          }
          mbar_wait(bars + B_MMADONE, pmma); pmma ^= 1;
#pragma unroll 1
          for (s = 0; s < 7; s++) {
            acquire(s, 16384 + 12288);
            tma_ld(sb + s * 28672, &p.tmWsp, s * 64, row0, bars + B_FULL + 8 * s);
          }
          {
            const uint32_t zmask = sb + SM_ZMASK + layer * 4;
            uint32_t ready = 0;
            s = 0;
#pragma unroll 1
            for (int kb = 0; kb < 32; kb++) {
              if (kb >= 7) {
                acquire(s, 16384 + 12288);
                tma_ld(sb + s * 28672, &p.tmWsp, kb * 64, row0, bars + B_FULL + 8 * s);
              }
              if (!((ready >> kb) & 1)) { ready = wait_smem_bit(zmask, kb); fence_async_global(); }
              if (kb == 0) TSP(72 + layer * 24);
              if (kb == 5) { mbar_wait(bars + B_STGFREE, pstg); pstg ^= 1; }
              tma_ld(sb + s * 28672 + 16384, &p.tmZ, kb * 64, 96 * j, bars + B_FULL + 8 * s);
              s = (s + 1 == 7) ? 0 : s + 1;
            }
          }
          peek(4);
          mbar_expect_tx(bars + B_BFULL, 40960);
          bulk_ld(sb + SM_WO + 20480, wz, 20480, bars + B_BFULL);
          peek(5);
          bulk_ld(sb + SM_WO + 40960, wz + 20480, 20480, bars + B_BFULL);
          peek(6);
          mbar_expect_tx(bars + B_BFULL1, 61440);
          bulk_ld(sb + SM_WO + 61440, wz + 40960, 40960, bars + B_BFULL1);
          mbar_wait(bars + B_MMADONE, pmma); pmma ^= 1;
#pragma unroll 1
          for (s = 0; s < 3; s++) acquire(s, 32768);
          wait_flag(g_flags + (F_U + layer * 16 + r) * 32, e1 * 8);
          TSP(73 + layer * 24);
#pragma unroll
          for (int kb = 0; kb < 6; kb++) tma_ld(sb + kb * 16384, &p.tmU64, kb * 64, row0, bars + B_FULL + 8 * (kb >> 1));
          bulk_ld(sb + SM_WO, wz + 81920, 20480, bars + B_BFULL1);
#pragma unroll 1
          for (s = 0; s < 3; s++) {
            acquire(s, s == 2 ? 32768 + 20480 : 32768);
            tma_ld(sb + s * 32768, &p.tmU64, (2 * s + 6) * 64, row0, bars + B_FULL + 8 * s);
            tma_ld(sb + s * 32768 + 16384, &p.tmU64, (2 * s + 7) * 64, row0, bars + B_FULL + 8 * s);
            if (s == 2) bulk_ld(sb + SM_WO + 20480, wz + 102400, 20480, bars + B_FULL + 16);
          }
          if (layer == 0) {
            peek(0);
            acquire(3, 16384 + 30720);
            bulk_ld(sb + 3 * 47104 + 16384, wb, 30720, bars + B_FULL + 24);
          }
          mbar_wait(bars + B_MMADONE, pmma); pmma ^= 1;
        }
      }
      __syncwarp();
    } else if (warp == 9) {
      if (elect_one()) {
        uint32_t ng = 0;
        auto go = [&]() { mbar_wait(bars + B_STGO + 8 * (ng & 1), (ng >> 1) & 1); ng++; };
        auto done = [&](int flag) { bulk_commit(); bulk_wait_all(); signal_flag(g_flags + flag * 32); };
        if (b < 80) {
          const int g = b / 10, kb = b % 10;
          bulk_st(g_wqkv + (size_t)b * 30720, sb + P0_IMG0, 30720);
          bulk_st(g_csq + (kb * 8 + g) * 240, sb + P0_CS2, 960);
          bulk_st(g_kv + g * 3840 + kb * 384, sb + P0_ZERO, 1536);
          bulk_st(g_kv + (8 + g) * 3840 + kb * 384, sb + P0_ZERO, 1536);
          bulk_commit(); bulk_wait_read();
          mbar_arrive(bars + B_P0A);
          bulk_wait_all();
          signal_flag(g_flags + (F_WQ + g) * 32);
        } else {
          const int i0 = b - 80;
          bulk_st(g_win + (size_t)i0 * 24576, sb + P0_IMG0, 24576);
          bulk_st(g_csi + ((i0 % 10) * 8 + i0 / 10) * 192, sb + P0_CS2, 768);
          bulk_commit(); bulk_wait_read();
          mbar_arrive(bars + B_P0A);
        }
        TSP(113);
        go();
        if (b < 80) {
          bulk_st(g_wo + (size_t)b * 10240, sb + P0_IMG1, 10240);
          bulk_st(g_wout + (size_t)b * 10240, sb + P0_IMG1 + 10240, 10240);
        } else if (b < 112) {
          const int i1 = b - 80 + 48;
          bulk_st(g_win + (size_t)i1 * 24576, sb + P0_IMG1, 24576);
          bulk_st(g_csi + ((i1 % 10) * 8 + i1 / 10) * 192, sb + P0_CS3, 768);
        } else {
          bulk_st(g_wout + (size_t)(80 + b - 112) * 10240, sb + P0_IMG1, 10240);
        }
        bulk_commit(); bulk_wait_read();
        mbar_arrive(bars + B_P0B);
        bulk_wait_all();
        signal_flag(g_flags + F_WREST * 32);
        TSP(115);
        {
          const uint8_t* w = reinterpret_cast<const uint8_t*>(p.wsp) + (size_t)b * 65536;
#pragma unroll
          for (int i = 0; i < 4; i++) prefetch_l2_bulk(w + i * 16384, 16384);
        }
#pragma unroll 1
        for (int layer = 0; layer < 2; layer++) {
          go(); bulk_red_f32(g_kv + (layer * 8 + j) * 3840, sb + SM_KVS, 15360); done(F_KV + layer * 8 + j); TSP(74 + layer * 24);
          go(); tma_st(&p.tmO80, sb + SM_OST, 80 * j, row0); done(F_O + layer * 16 + r); TSP(75 + layer * 24);
          go(); tma_st(&p.tmX80, sb + SM_XT, 80 * j, row0 + (layer == 0 ? 0 : 2 * S_)); done(F_X1 + layer * 16 + r); TSP(76 + layer * 24);
          go(); tma_st(&p.tmZ, sb + SM_ZT0, row0, 96 * j); tma_st(&p.tmZ, sb + SM_ZT1, row0 + 64, 96 * j);
          bulk_commit(); bulk_wait_all();
          signal_flag(g_flags + (F_ZN + layer * 8 + j) * 32 + r);
          mbar_arrive(bars + B_STGFREE); TSP(78 + layer * 24);
          go(); tma_st(&p.tmU64, sb + SM_UST, 96 * j, row0); tma_st(&p.tmUs32, sb + SM_UST + 16384, 96 * j + 64, row0);
          done(F_U + layer * 16 + r); TSP(79 + layer * 24);
          go();
          if (layer == 0) {
            tma_st(&p.tmX80, sb + SM_XT, 80 * j, row0 + S_); done(F_X2 + r); TSP(80);
          } else {
            tma_st(&p.tmOut80, sb + SM_XT, 80 * j, row0);
            bulk_commit(); bulk_wait_all();
          }
        }
      }
      __syncwarp();
    } else {
      const int t = tid - 320;
#pragma unroll 1
      for (int it = 0; it < 4; it++) {
        if (it == 0) {
          if (t == 0) wait_flag(g_flags + (F_WQ + j) * 32, e1 * 10);
          bar_sync(4, 64);
#pragma unroll 1
          for (int n = t; n < 240; n += 64) {
            float s = 0.f;
#pragma unroll
            for (int kb = 0; kb < 10; kb++) s += ld_cg_f(g_csq + (kb * 8 + j) * 240 + n);
            const int jj = n >> 3, q = (n >> 1) & 3, e = 2 * jj + (n & 1);
            asm volatile("st.shared.f32 [%0], %1;" ::"r"(sb + SM_CSQ + (q * 60 + e) * 4), "f"(s) : "memory");
          }
#pragma unroll 1
          for (int n = t; n < 128; n += 64)
            asm volatile("st.shared.f32 [%0], %1;" ::"r"(sb + SM_BSP + n * 4), "f"(__bfloat162float(p.bsp[row0 + n])) : "memory");
        } else if (it == 1) {
          if (t == 0) wait_flag(g_flags + F_WREST * 32, e1 * 128);
          bar_sync(4, 64);
#pragma unroll 1
          for (int n = t; n < 192; n += 64) {
            float s = 0.f;
#pragma unroll
            for (int kb = 0; kb < 10; kb++) s += ld_cg_f(g_csi + (kb * 8 + j) * 192 + n);
            asm volatile("st.shared.f32 [%0], %1;" ::"r"(sb + SM_CSI + n * 4), "f"(s) : "memory");
          }
        }
        mbar_wait(bars + B_XSLOC, it & 1);
#pragma unroll
        for (int h = 0; h < 2; h++) {
          const int row = t + 64 * h;
          float2 pt[8];
          uint32_t spins = 0;
          while (true) {
            const uint4* xs = g_xstat + r * 8 * 128 + row;
            const uint32_t tag = e1 * 4 + it;
            bool ok = ld_tagged<0>(xs, tag, pt[0]);
            ok &= ld_tagged<128>(xs, tag, pt[1]); ok &= ld_tagged<256>(xs, tag, pt[2]); ok &= ld_tagged<384>(xs, tag, pt[3]);
            ok &= ld_tagged<512>(xs, tag, pt[4]); ok &= ld_tagged<640>(xs, tag, pt[5]); ok &= ld_tagged<768>(xs, tag, pt[6]);
            ok &= ld_tagged<896>(xs, tag, pt[7]);
            if (ok) break;
            trap_if(++spins > SPIN_LIMIT);
            __nanosleep(100);
          }
          float mean, rstd;
          combine_stats(pt, 80.f, mean, rstd);
          sts64f(sb + SM_ROWSTAT + row * 8, mean, rstd);
        }
        __syncwarp();
        if (lane == 0) mbar_arrive(bars + B_XSFULL);
        if ((it & 1) && warp == 10) {
          const int layer = it >> 1;
          const uint32_t* zf = g_flags + (F_ZN + layer * 8 + j) * 32;
          uint32_t mask = 0, spins = 0;
          mbar_wait(bars + B_ZNLOC, layer);
          while (mask != 0xffffffffu) {
            const uint32_t m = __ballot_sync(0xffffffffu, (int32_t)(ld_acquire(zf + (lane >> 1)) - e1) >= 0);
            if (m != mask) { mask = m; if (lane == 0) sts32(sb + SM_ZMASK + layer * 4, mask); }
            trap_if(++spins > SPIN_LIMIT);
          }
        }
      }
    }
  } else {
    asm volatile("setmaxnreg.inc.sync.aligned.u32 208;");
    const int wg = warp >> 2, w = warp & 3, q = lane & 3, rw = lane >> 2;
    const bool elect = (tid & 127) == 0;
    uint32_t ph = 0, pxs = 0, pbf = 0;
    const int R0 = 64 * wg + 16 * w + rw;
    uint32_t ng = 0;
    auto stage_done = [&]() { fence_async_smem(); __syncwarp(); if (lane == 0) mbar_arrive(bars + B_STGO + 8 * (ng & 1)); ng++; };
    uint4* const xstat = g_xstat + (r * 8 + j) * 128;
    prologue_stage1(sb, b, warp, lane, xstat, e1 * 4);
    ng = 1;
#pragma unroll 1
    for (int layer = 0; layer < 2; layer++) {
      {
        float acc[120];
        mainloop<240, 4, 47104, 1, false, 3>(acc, 10, sb, 16384, 3 * layer, wg, elect, ph, 64 + layer * 24);
        TS(4 + layer * 24);
        mbar_wait(bars + B_XSFULL, pxs); pxs ^= 1;
        const uint32_t csa = sb + SM_CSQ + q * 240;
        float sa[2], nm[2], va[2], vt[2];
#pragma unroll
        for (int h = 0; h < 2; h++) {
          const float2 ms = lds64f(sb + SM_ROWSTAT + (R0 + 8 * h) * 8);
          va[h] = ms.y; vt[h] = -ms.x * ms.y;
          sa[h] = ms.y * 1.4426950408889634f; nm[h] = -ms.x;
        }
        const uint32_t rowoff0 = (R0 >> 3) * 128 + (R0 & 7) * 16;
        auto affine = [&](int base, uint32_t csoff, int h, float (&y)[20]) {
#pragma unroll
          for (int i = 0; i < 5; i++) {
            const float4 c = lds128f(csa + csoff + i * 16);
            y[4 * i + 0] = fmaf(c.x, nm[h], acc[base + 8 * i + 2 * h]);
            y[4 * i + 1] = fmaf(c.y, nm[h], acc[base + 8 * i + 2 * h + 1]);
            y[4 * i + 2] = fmaf(c.z, nm[h], acc[base + 8 * i + 4 + 2 * h]);
            y[4 * i + 3] = fmaf(c.w, nm[h], acc[base + 8 * i + 4 + 2 * h + 1]);
          }
        };
        bar_sync(1, 256);
        TS(19 + layer * 24);
#pragma unroll
        for (int h = 0; h < 2; h++) {
          uint32_t vv[10];
#pragma unroll
          for (int i = 0; i < 5; i++) {
            const float4 c = lds128f(csa + 160 + i * 16);
            vv[2 * i] = pack_bf16(fmaf(c.x, vt[h], acc[80 + 8 * i + 2 * h] * va[h]), fmaf(c.y, vt[h], acc[80 + 8 * i + 2 * h + 1] * va[h]));
            vv[2 * i + 1] = pack_bf16(fmaf(c.z, vt[h], acc[80 + 8 * i + 4 + 2 * h] * va[h]), fmaf(c.w, vt[h], acc[80 + 8 * i + 4 + 2 * h + 1] * va[h]));
          }
          const uint32_t vb = sb + SM_VST + q * VST_HEAD + rowoff0 + h * 128;
          sts128(vb, vv[0], vv[1], vv[2], vv[3]);
          sts128(vb + 2048, vv[4], vv[5], vv[6], vv[7]);
          sts128(vb + 4096, vv[8], vv[9], 0x00003f80u, 0u);
        }
        {
          float y0[20], y1[20];
          affine(40, 80, 0, y0); affine(40, 80, 1, y1);
          feature_map2<false>(y0, y1, sa[0], sa[1], sb + SM_PHI + q * PHI_HEAD + rowoff0);
        }
        TS(20 + layer * 24);
        fence_async_smem();
        bar_sync(1, 256);
        TS(21 + layer * 24);
        {
          float kva[20], kvb[20];
#pragma unroll
          for (int i = 0; i < 20; i++) { kva[i] = 0.f; kvb[i] = 0.f; }
          const uint32_t h0 = 2 * wg;
          const uint64_t dv = make_desc(sb + SM_VST + h0 * VST_HEAD, 128, 2048, 0), dp = make_desc(sb + SM_PHI + h0 * PHI_HEAD, 128, 2048, 0);
          fence_regs(kva); fence_regs(kvb);
          wgmma_fence();
#pragma unroll
          for (int ks = 0; ks < 8; ks++) {
            wgmma_ss_n40<1, 1>(kva, dv + ks * 16, dp + ks * 16, 1);
            wgmma_ss_n40<1, 1>(kvb, dv + (VST_HEAD >> 4) + ks * 16, dp + (PHI_HEAD >> 4) + ks * 16, 1);
          }
          wgmma_commit();
          wgmma_wait<0>();
          fence_regs(kva); fence_regs(kvb);
          TS(22 + layer * 24);
          if (w < 2) {
#pragma unroll
            for (int h = 0; h < 2; h++) {
              const int d = 16 * w + 8 * h + rw;
              if (d < 24) {
#pragma unroll
                for (int jj = 0; jj < 5; jj++) {
                  sts64f(sb + SM_KVS + ((h0 * 24 + d) * 40 + 8 * jj + 2 * q) * 4, kva[4 * jj + 2 * h], kva[4 * jj + 2 * h + 1]);
                  sts64f(sb + SM_KVS + (((h0 + 1) * 24 + d) * 40 + 8 * jj + 2 * q) * 4, kvb[4 * jj + 2 * h], kvb[4 * jj + 2 * h + 1]);
                }
              }
            }
          }
        }
        stage_done();
        bar_sync(1, 256);
        TS(5 + layer * 24);
        {
          float y0[20], y1[20];
          affine(0, 0, 0, y0); affine(0, 0, 1, y1);
          feature_map2<true>(y0, y1, sa[0], sa[1], sb + SM_PHI + q * PHI_HEAD + rowoff0);
        }
      }
      TS(6 + layer * 24);
      {
        if (tid < 96) sts128(sb + SM_KVB + (tid / 24) * KVB_HEAD + ((tid % 24) >> 3) * 768 + 5 * 128 + (tid & 7) * 16, 0u, 0u, 0u, 0u);
        if (lane == 0) wait_flag(g_flags + (F_KV + layer * 8 + j) * 32, e1 * 16);
        __syncwarp();
        TS(7 + layer * 24);
        const float* kvg = g_kv + (layer * 8 + j) * 3840;
        float4 la[2], lc[2];
#pragma unroll
        for (int u = 0; u < 2; u++) {
          const int i = tid + 256 * u;
          if (i < 480) { la[u] = ld_cg_f4(kvg + i * 8); lc[u] = ld_cg_f4(kvg + i * 8 + 4); }
        }
#pragma unroll
        for (int u = 0; u < 2; u++) {
          const int i = tid + 256 * u;
          if (i < 480) {
            const int hd = i / 120, n = (i % 120) / 5, kg = i % 5;
            sts128(sb + SM_KVB + hd * KVB_HEAD + (n >> 3) * 768 + kg * 128 + (n & 7) * 16, pack_bf16(la[u].x, la[u].y), pack_bf16(la[u].z, la[u].w),
                   pack_bf16(lc[u].x, lc[u].y), pack_bf16(lc[u].z, lc[u].w));
          }
        }
        fence_async_smem();
        bar_sync(1, 256);
        TS(24 + layer * 24);
        float oa[4][12];
#pragma unroll
        for (int hd = 0; hd < 4; hd++)
#pragma unroll
          for (int i = 0; i < 12; i++) oa[hd][i] = 0.f;
#pragma unroll
        for (int hd = 0; hd < 4; hd++) fence_regs(oa[hd]);
        const uint64_t dq = make_desc(sb + SM_PHI + wg * 1024, 2048, 128, 0), dk = make_desc(sb + SM_KVB, 128, 768, 0);
        wgmma_fence();
#pragma unroll
        for (int hd = 0; hd < 4; hd++)
#pragma unroll
          for (int ks = 0; ks < 3; ks++)
            wgmma_ss_n24<0, 0>(oa[hd], dq + hd * (PHI_HEAD >> 4) + ks * 256, dk + hd * (KVB_HEAD >> 4) + ks * 16, 1);
        wgmma_commit();
        wgmma_wait<0>();
#pragma unroll
        for (int hd = 0; hd < 4; hd++) fence_regs(oa[hd]);
        TS(25 + layer * 24);
#pragma unroll
        for (int hd = 0; hd < 4; hd++)
#pragma unroll
          for (int h = 0; h < 2; h++) {
            const float inv = rcp(__shfl_sync(0xffffffffu, oa[hd][8 + 2 * h], (lane & ~3) | 2) + 1e-6f);
            const uint32_t ob = sb + SM_OST + (R0 + 8 * h) * 160 + hd * 40 + q * 4;
            sts32(ob, pack_bf16(oa[hd][2 * h] * inv, oa[hd][2 * h + 1] * inv));
            sts32(ob + 16, pack_bf16(oa[hd][4 + 2 * h] * inv, oa[hd][4 + 2 * h + 1] * inv));
            if (q < 2) sts32(ob + 32, pack_bf16(oa[hd][8 + 2 * h] * inv, oa[hd][8 + 2 * h + 1] * inv));
          }
        stage_done();
      }
      TS(8 + layer * 24);
      {
        float acc[40];
        uint32_t xr[5][4];
        residual_load(xr, residual_addr(sb, wg, w, lane));
        mainloop<80, 3, 32768, 2, true, 0>(acc, 5, sb, SM_WO, 0, wg, elect, ph, 65 + layer * 24, pbf);
        pbf ^= 1;
        TS(9 + layer * 24);
        float v[2][20];
        residual_update(acc, xr, v, residual_addr(sb, wg, w, lane));
        stage_done();
        TS(10 + layer * 24);
#pragma unroll
        for (int h = 0; h < 2; h++) {
          float mean, m2;
          row_partial_stats<20>(v[h], 1.f / 80.f, mean, m2);
          if (q == 0) st_tagged(xstat + R0 + 8 * h, mean, m2, e1 * 4 + 1 + 2 * layer);
        }
        if (lane == 0) mbar_arrive(bars + B_XSLOC);
      }
      uint32_t z1p[24];
      {
        float acc[96];
        mainloop<192, 5, 40960, 1, false, 3>(acc, 10, sb, 16384, 3, wg, elect, ph, 66 + layer * 24);
        TS(11 + layer * 24);
        mbar_wait(bars + B_XSFULL, pxs); pxs ^= 1;
        float la[2], lt[2];
#pragma unroll
        for (int h = 0; h < 2; h++) {
          const float2 ms = lds64f(sb + SM_ROWSTAT + (R0 + 8 * h) * 8);
          la[h] = 0.5f * ms.y; lt[h] = -ms.x * la[h];
        }
#pragma unroll
        for (int jj = 0; jj < 12; jj++) {
          const float2 c = lds64f(sb + SM_CSI + (8 * jj + 2 * q) * 4);
#pragma unroll
          for (int h = 0; h < 2; h++) {
            acc[4 * jj + 2 * h] = gelu_half(fmaf(c.x, lt[h], acc[4 * jj + 2 * h] * la[h]));
            acc[4 * jj + 2 * h + 1] = gelu_half(fmaf(c.y, lt[h], acc[4 * jj + 2 * h + 1] * la[h]));
          }
        }
#pragma unroll
        for (int h = 0; h < 2; h++) {
          float v[24];
#pragma unroll
          for (int jj = 0; jj < 12; jj++) { v[2 * jj] = acc[4 * jj + 2 * h]; v[2 * jj + 1] = acc[4 * jj + 2 * h + 1]; }
          float mean, m2;
          row_partial_stats<24>(v, 1.f / 96.f, mean, m2);
          if (q == 0) st_tagged(g_zstat + (r * 8 + j) * 128 + R0 + 8 * h, mean, m2, e1 * 2 + layer);
        }
        TS(12 + layer * 24);
#pragma unroll
        for (int jj = 0; jj < 12; jj++) {
          const float2 c = lds64f(sb + SM_CSI + (96 + 8 * jj + 2 * q) * 4);
#pragma unroll
          for (int h = 0; h < 2; h++)
            z1p[2 * jj + h] = pack_bf16(gelu_half(fmaf(c.x, lt[h], acc[48 + 4 * jj + 2 * h] * la[h])),
                                        gelu_half(fmaf(c.y, lt[h], acc[48 + 4 * jj + 2 * h + 1] * la[h])));
        }
        float2 p0[2], p1[2];
        {
          const uint4* zs = g_zstat + (r * 8 + 2 * q) * 128 + R0;
          uint32_t spins = 0;
          while (true) {
            bool ok = ld_tagged<0>(zs, e1 * 2 + layer, p0[0]);
            ok &= ld_tagged<128>(zs, e1 * 2 + layer, p1[0]);
            ok &= ld_tagged<8>(zs, e1 * 2 + layer, p0[1]);
            ok &= ld_tagged<136>(zs, e1 * 2 + layer, p1[1]);
            if (__all_sync(0xffffffffu, ok)) break;
            trap_if(++spins > SPIN_LIMIT);
          }
        }
        bar_sync(1, 256);
        TS(13 + layer * 24);
        float zm[2], zr[2];
#pragma unroll
        for (int h = 0; h < 2; h++) {
          float m = p0[h].x + p1[h].x;
          m += __shfl_xor_sync(0xffffffffu, m, 1);
          m += __shfl_xor_sync(0xffffffffu, m, 2);
          m *= 0.125f;
          const float d0 = p0[h].x - m, d1 = p1[h].x - m;
          float m2 = p0[h].y + p1[h].y + 96.f * (d0 * d0 + d1 * d1);
          m2 += __shfl_xor_sync(0xffffffffu, m2, 1);
          m2 += __shfl_xor_sync(0xffffffffu, m2, 2);
          zr[h] = rsqrtf(m2 * (1.f / 768.f) + 1e-5f);
          zm[h] = -m * zr[h];
        }
        const uint32_t zb = sb + (wg == 0 ? SM_ZT0 : SM_ZT1);
#pragma unroll
        for (int t = 0; t < 6; t++) {
          uint32_t x[4];
#pragma unroll
          for (int m = 0; m < 4; m++) {
            const int h = m & 1, jj = 2 * t + (m >> 1);
            x[m] = pack_bf16(fmaf(acc[4 * jj + 2 * h], zr[h], zm[h]), fmaf(acc[4 * jj + 2 * h + 1], zr[h], zm[h]));
          }
          const int m = lane >> 3, i = lane & 7, f = 8 * (2 * t + (m >> 1)) + i, c = 2 * w + (m & 1);
          stsm4t(zb + f * 128 + ((c ^ i) << 4), x[0], x[1], x[2], x[3]);
        }
        stage_done();
        if (tid == 0) mbar_arrive(bars + B_ZNLOC);
      }
      TS(14 + layer * 24);
      {
        float acc[48];
        mainloop<96, 7, 28672, 1, false, 0>(acc, 32, sb, 16384, 0, wg, elect, ph, 67 + layer * 24);
        TS(15 + layer * 24);
        bar_sync(1, 256);
        const float b0 = lds32f(sb + SM_BSP + R0 * 4), b1 = lds32f(sb + SM_BSP + (R0 + 8) * 4);
        const int m = lane >> 3, row = 64 * wg + 16 * w + 8 * (m & 1) + (lane & 7);
#pragma unroll
        for (int t = 0; t < 6; t++) {
          uint32_t x[4];
#pragma unroll
          for (int mm = 0; mm < 4; mm++) {
            const int h = mm & 1, jj = 2 * t + (mm >> 1);
            const float bb = h ? b1 : b0;
            const uint32_t z = z1p[2 * jj + h];
            x[mm] = pack_bf16(bf_lo(z) * (acc[4 * jj + 2 * h] + bb), bf_hi(z) * (acc[4 * jj + 2 * h + 1] + bb));
          }
          const int jj = 2 * t + (m >> 1);
          const uint32_t a = t < 4 ? sb + SM_UST + row * 128 + ((jj ^ (row & 7)) << 4)
                                   : sb + SM_UST + 16384 + row * 64 + (((jj - 8) ^ ((row >> 1) & 3)) << 4);
          stsm4(a, x[0], x[1], x[2], x[3]);
        }
        stage_done();
      }
      TS(16 + layer * 24);
      {
        float acc[40];
        uint32_t xr[5][4];
        residual_load(xr, residual_addr(sb, wg, w, lane));
        mainloop<80, 3, 32768, 2, true, 0>(acc, 6, sb, SM_WO, 0, wg, elect, ph, 68 + layer * 24, pbf);
        pbf ^= 1;
        TS(17 + layer * 24);
        float v[2][20];
        residual_update(acc, xr, v, residual_addr(sb, wg, w, lane));
        stage_done();
        TS(18 + layer * 24);
        if (layer == 0) {
#pragma unroll
          for (int h = 0; h < 2; h++) {
            float mean, m2;
            row_partial_stats<20>(v[h], 1.f / 80.f, mean, m2);
            if (q == 0) st_tagged(xstat + R0 + 8 * h, mean, m2, e1 * 4 + 2);
          }
          if (lane == 0) mbar_arrive(bars + B_XSLOC);
        }
      }
    }
  }
}

typedef CUresult (*EncodeFn)(CUtensorMap*, CUtensorMapDataType, cuuint32_t, void*, const cuuint64_t*, const cuuint64_t*, const cuuint32_t*,
                             const cuuint32_t*, CUtensorMapInterleave, CUtensorMapSwizzle, CUtensorMapL2promotion, CUtensorMapFloatOOBfill);

void make_map(EncodeFn enc, CUtensorMap* tm, const void* ptr, uint64_t rows, uint64_t cols, uint32_t box_rows, uint32_t box_cols, CUtensorMapSwizzle sw) {
  cuuint64_t dims[2] = {cols, rows};
  cuuint64_t strides[1] = {cols * 2};
  cuuint32_t box[2] = {box_cols, box_rows};
  cuuint32_t es[2] = {1, 1};
  enc(tm, CU_TENSOR_MAP_DATA_TYPE_BFLOAT16, 2, const_cast<void*>(ptr), dims, strides, box, es, CU_TENSOR_MAP_INTERLEAVE_NONE, sw,
      CU_TENSOR_MAP_L2_PROMOTION_L2_256B, CU_TENSOR_MAP_FLOAT_OOB_FILL_NONE);
}

}

extern "C" void kernel_launch(void* const* d_in, const int* in_sizes, int n_in, void* d_out, int out_size) {
  (void)in_sizes; (void)n_in; (void)out_size;
  static EncodeFn enc = nullptr;
  static void *px = nullptr, *po = nullptr, *pu = nullptr, *pz = nullptr;
  if (!enc) {
    void* fn = nullptr;
    cudaDriverEntryPointQueryResult st;
    cudaGetDriverEntryPoint("cuTensorMapEncodeTiled", &fn, cudaEnableDefault, &st);
    enc = (EncodeFn)fn;
    cudaGetSymbolAddress(&px, g_x); cudaGetSymbolAddress(&po, g_o); cudaGetSymbolAddress(&pu, g_u); cudaGetSymbolAddress(&pz, g_zt);
    cudaFuncSetAttribute(fused_kernel, cudaFuncAttributeMaxDynamicSharedMemorySize, SMEM_BYTES);
  }
  Params p;
  const void* ax = d_in[0];
  const CUtensorMapSwizzle S128 = CU_TENSOR_MAP_SWIZZLE_128B, S64 = CU_TENSOR_MAP_SWIZZLE_64B, S0 = CU_TENSOR_MAP_SWIZZLE_NONE;
  make_map(enc, &p.tmAx64, ax, S_, D_, 128, 64, S128);
  make_map(enc, &p.tmAx80, ax, S_, D_, 128, 80, S0);
  make_map(enc, &p.tmX64, px, 3 * S_, D_, 128, 64, S128);
  make_map(enc, &p.tmX80, px, 3 * S_, D_, 128, 80, S0);
  make_map(enc, &p.tmOut80, d_out, S_, D_, 128, 80, S0);
  make_map(enc, &p.tmO64, po, S_, D_, 128, 64, S128);
  make_map(enc, &p.tmO80, po, S_, D_, 128, 80, S0);
  make_map(enc, &p.tmU64, pu, S_, FH_, 128, 64, S128);
  make_map(enc, &p.tmUs32, pu, S_, FH_, 128, 32, S64);
  make_map(enc, &p.tmZ, pz, FH_, S_, 96, 64, S128);
  make_map(enc, &p.tmWsp, d_in[6], S_, S_, 128, 64, S128);
  make_map(enc, &p.tmWo, d_in[3], D_, D_, 64, 80, S0);
  make_map(enc, &p.tmWi, d_in[5], D_, 2 * FH_, 64, 96, S0);
  make_map(enc, &p.tmWout, d_in[8], FH_, D_, 64, 80, S0);
  p.wqkv = (const __nv_bfloat16*)d_in[1];
  p.wphi = (const __nv_bfloat16*)d_in[2];
  p.wsp = (const __nv_bfloat16*)d_in[6];
  p.bsp = (const __nv_bfloat16*)d_in[7];
  fused_kernel<<<NCTA, NTHREADS, SMEM_BYTES, cudaStreamPerThread>>>(p);
}
```
